```python
import torch

def _softmax(x, axis=-1):
    return torch.softmax(x, dim=axis)
def _gelu(x):
    return torch.nn.functional.gelu(x, approximate="tanh")
def _silu(x):
    return torch.nn.functional.silu(x)
def _sigmoid(x):
    return torch.sigmoid(x)
def _layernorm(x, axis=-1, eps=1e-5):
    m = x.mean(dim=axis, keepdim=True)
    v = x.var(dim=axis, keepdim=True, unbiased=False)
    return (x - m) / torch.sqrt(v + eps)
def _scatter_add(tgt, idx, src, axis=0):
    return tgt.clone().index_add_(axis, idx, src)
def _segment_sum(src, seg, n):
    out = torch.zeros((n,) + src.shape[1:], dtype=src.dtype)
    return out.index_add_(0, seg, src)
def _pad(x, pw):
    flat = tuple(v for pair in reversed(pw) for v in pair)
    return torch.nn.functional.pad(x, flat)

kernel_name = 'standalone__deep_cross_fibinet__recsys'

def setup_inputs():

    _w = (lambda a: (lambda t: t.to(torch.bfloat16) if t.is_floating_point() else t)(torch.as_tensor(a)))
    B, F, D = 4096, 26, 128
    V = min(1000000, 100000)
    Fr = max(F // 2, 1)
    H = min(F * D, 256)
    return {
        "idx": _w((lambda lo, hi, *s: torch.randint(lo, hi, s))(0, V, B, F).to(torch.int64)),
        "table": _w((lambda *s: torch.randn(*s, dtype=torch.bfloat16) * 1.6)(V, D)),
        "se_w1": _w((lambda *s: torch.randn(*s, dtype=torch.bfloat16) * 1.6)(F, Fr)),
        "se_w2": _w((lambda *s: torch.randn(*s, dtype=torch.bfloat16) * 1.6)(Fr, F)),
        "w_bi": _w((lambda *s: torch.randn(*s, dtype=torch.bfloat16) * 0.05)(D, D) * (D ** -0.5)),
        "w_cross": _w((lambda *s: torch.randn(*s, dtype=torch.bfloat16) * 0.05)(2 * F * F * D) * 0.01),
        "w_deep1": _w((lambda *s: torch.randn(*s, dtype=torch.bfloat16) * 0.8)(F * D, H) * ((F * D) ** -0.5)),
        "w_deep2": _w((lambda *s: torch.randn(*s, dtype=torch.bfloat16) * 0.05)(H) * 0.01),
    }

def reference(idx, table, se_w1, se_w2, w_bi, w_cross, w_deep1, w_deep2):
    emb = table[idx]
    B = emb.shape[0]
    z = emb.mean(axis=-1)
    a = _sigmoid(_gelu(z @ se_w1) @ se_w2)
    v = a[:, :, None] * emb
    eW = torch.einsum('bfd,de->bfe', emb, w_bi)
    vW = torch.einsum('bfd,de->bfe', v, w_bi)
    p = torch.einsum('bie,bje->bije', eW, emb).reshape(B, -1)
    q = torch.einsum('bie,bje->bije', vW, v).reshape(B, -1)
    cross_feat = torch.concatenate([p, q], axis=-1)
    logit_cross = cross_feat @ w_cross
    h = _gelu(emb.reshape(B, -1) @ w_deep1)
    logit_deep = h @ w_deep2
    return logit_cross + logit_deep
```

```cpp
#include <cuda_runtime.h>
#include <cuda_bf16.h>
#include <cuda.h>
#include <stdint.h>

namespace {

constexpr int NCTA = 128;
constexpr int NTHREADS = 384;

constexpr uint32_t OFF_E0 = 0;
constexpr uint32_t OFF_R1 = 13 * 8192;
constexpr uint32_t OFF_WR = OFF_R1 + 4 * 8192;
constexpr uint32_t OFF_WT = OFF_WR + 65536;
constexpr uint32_t OFF_SE = OFF_WT + 20480;
constexpr uint32_t OFF_W2 = OFF_SE + 2048;
constexpr uint32_t OFF_RES = OFF_W2 + 1024;
constexpr uint32_t OFF_BAR = OFF_RES + 512;
constexpr uint32_t SMEM_USED = OFF_BAR + 1024;
constexpr uint32_t SMEM_BYTES = SMEM_USED;

constexpr uint32_t GSLOT = 7168, GBYTES = 6912, NGS = 9;
constexpr uint32_t OFF_XCH = OFF_WR + 32768;

constexpr int B_WFULL = 0, B_WEMPTY = 4, B_DFULL = 8, B_DDONE = 21, B_XFULL = 34, B_XDONE = 47,
              B_YFULL = 60, B_YDONE = 69, B_GFULL = 78, B_GEMPTY = 87, B_WT1 = 96, B_CANSEND = 97,
              B_XCHF = 98, B_XCONS = 99, NBAR = 100;

__device__ uint4 g_G[64 * GBYTES / 16];
__device__ uint4 g_WT1[20480 / 16];
__device__ unsigned int g_ready;
#define DBG_T(i) do {} while (0)

__device__ __forceinline__ uint32_t smem_u32(const void* p) { return (uint32_t)__cvta_generic_to_shared(p); }

__device__ __forceinline__ void mbar_init(uint32_t b, uint32_t c) {
    asm volatile("mbarrier.init.shared::cta.b64 [%0], %1;" ::"r"(b), "r"(c) : "memory");
}
__device__ __forceinline__ void mbar_wait(uint32_t b, uint32_t ph) {
    asm volatile(
        "{\n.reg .pred p;\n.reg .u32 c;\nmov.u32 c, 0;\n"
        "LW:\nmbarrier.try_wait.parity.shared::cta.b64 p, [%0], %1;\n@p bra LD;\n"
        "add.u32 c, c, 1;\nsetp.lt.u32 p, c, 2000000;\n@p bra LW;\ntrap;\nLD:\n}\n" ::"r"(b), "r"(ph) : "memory");
}
__device__ __forceinline__ void mbar_wait_cluster(uint32_t b, uint32_t ph) {
    asm volatile(
        "{\n.reg .pred p;\n.reg .u32 c;\nmov.u32 c, 0;\n"
        "LW:\nmbarrier.try_wait.parity.acquire.cluster.shared::cta.b64 p, [%0], %1;\n@p bra LD;\n"
        "add.u32 c, c, 1;\nsetp.lt.u32 p, c, 2000000;\n@p bra LW;\ntrap;\nLD:\n}\n" ::"r"(b), "r"(ph) : "memory");
}
__device__ __forceinline__ void mbar_arrive_elect(uint32_t b) {
    asm volatile("{\n.reg .pred p;\nelect.sync _|p, 0xffffffff;\n@p mbarrier.arrive.shared::cta.b64 _, [%0];\n}\n" ::"r"(b) : "memory");
}
__device__ __forceinline__ void mbar_arrive_remote_elect(uint32_t rb) {
    asm volatile("{\n.reg .pred p;\nelect.sync _|p, 0xffffffff;\n@p mbarrier.arrive.release.cluster.shared::cluster.b64 _, [%0];\n}\n" ::"r"(rb) : "memory");
}
__device__ __forceinline__ void cpasync_arrive(uint32_t b) {
    asm volatile("cp.async.mbarrier.arrive.noinc.shared::cta.b64 [%0];" ::"r"(b) : "memory");
}
__device__ __forceinline__ void cpasync16(uint32_t dst, const void* src) {
    asm volatile("cp.async.cg.shared.global [%0], [%1], 16;" ::"r"(dst), "l"(src) : "memory");
}
__device__ __forceinline__ void bulk_elect(uint32_t dst, const void* src, uint32_t bytes, uint32_t bar) {
    asm volatile(
        "{\n.reg .pred p;\nelect.sync _|p, 0xffffffff;\n"
        "@p mbarrier.arrive.expect_tx.shared::cta.b64 _, [%3], %2;\n"
        "@p cp.async.bulk.shared::cluster.global.mbarrier::complete_tx::bytes [%0], [%1], %2, [%3];\n}\n" ::"r"(dst), "l"(src), "r"(bytes), "r"(bar) : "memory");
}
__device__ __forceinline__ void tma3d_elect(uint32_t dst, const CUtensorMap* tm, int c1, uint32_t bar) {
    asm volatile(
        "{\n.reg .pred p;\nelect.sync _|p, 0xffffffff;\n"
        "@p mbarrier.arrive.expect_tx.shared::cta.b64 _, [%3], 16384;\n"
        "@p cp.async.bulk.tensor.3d.shared::cluster.global.mbarrier::complete_tx::bytes [%0], [%1, {0, %2, 0}], [%3];\n}\n" ::"r"(dst), "l"(tm), "r"(c1), "r"(bar) : "memory");
}
__device__ __forceinline__ uint32_t uni(uint32_t v) {
    uint32_t r;
    asm volatile("redux.sync.or.b32 %0, %1, 0xffffffff;" : "=r"(r) : "r"(v));
    return r;
}
__device__ __forceinline__ uint32_t vmov(uint32_t v) {
    uint32_t r;
    asm volatile("prmt.b32 %0, %1, %1, %2;" : "=r"(r) : "r"(v), "r"(0x3210u + (threadIdx.y << 16)));
    return r;
}
__device__ __forceinline__ void fence_async() { asm volatile("fence.proxy.async.shared::cta;" ::: "memory"); }
__device__ __forceinline__ void wg_fence() { asm volatile("wgmma.fence.sync.aligned;" ::: "memory"); }
__device__ __forceinline__ void wg_commit() { asm volatile("wgmma.commit_group.sync.aligned;" ::: "memory"); }
template <int N> __device__ __forceinline__ void wg_wait() { asm volatile("wgmma.wait_group.sync.aligned %0;" ::"n"(N) : "memory"); }
template <int N> __device__ __forceinline__ void reg_fence(float (&d)[N]) {
#pragma unroll
    for (int i = 0; i < N; i++) asm volatile("" : "+f"(d[i])::"memory");
}
__device__ __forceinline__ uint32_t pack_bf16(float lo, float hi) {
    uint32_t r;
    asm("cvt.rn.bf16x2.f32 %0, %1, %2;" : "=r"(r) : "f"(hi), "f"(lo));
    return r;
}
__device__ __forceinline__ float bf_lo(uint32_t w) { return __uint_as_float(w << 16); }
__device__ __forceinline__ float bf_hi(uint32_t w) { return __uint_as_float(w & 0xffff0000u); }
__device__ __forceinline__ uint32_t hmul2(uint32_t a, uint32_t b) {
    uint32_t r;
    asm("mul.rn.bf16x2 %0, %1, %2;" : "=r"(r) : "r"(a), "r"(b));
    return r;
}
__device__ __forceinline__ uint4 lds128(uint32_t a) {
    uint4 v;
    asm volatile("ld.shared.v4.u32 {%0,%1,%2,%3}, [%4];" : "=r"(v.x), "=r"(v.y), "=r"(v.z), "=r"(v.w) : "r"(a) : "memory");
    return v;
}
__device__ __forceinline__ uint4 ldg128(const void* p) {
    uint4 v;
    asm volatile("ld.global.nc.v4.u32 {%0,%1,%2,%3}, [%4];" : "=r"(v.x), "=r"(v.y), "=r"(v.z), "=r"(v.w) : "l"(p));
    return v;
}

constexpr uint32_t SBASE = 1024;
constexpr uint32_t DESC_HI = (1024u >> 4) | (1u << 30);
__host__ __device__ constexpr uint64_t cdesc(uint32_t off, uint32_t lbo) { return ((uint64_t)DESC_HI << 32) | ((SBASE + off) >> 4) | ((lbo >> 4) << 16); }
#define DESC_B(reg, imm) "add.u32 lo, " reg ", " imm ";\nmov.b64 db, {lo, hi};\n"
#define DESC_PRE "{\n.reg .b32 lo, hi;\n.reg .b64 db, da;\nmov.b32 hi, 0x40000040;\n"

#define F8(d, o) "+f"(d[o + 0]), "+f"(d[o + 1]), "+f"(d[o + 2]), "+f"(d[o + 3]), "+f"(d[o + 4]), "+f"(d[o + 5]), "+f"(d[o + 6]), "+f"(d[o + 7])
#define F4(d, o) "+f"(d[o + 0]), "+f"(d[o + 1]), "+f"(d[o + 2]), "+f"(d[o + 3])

template <int SC, uint32_t AOFF, uint32_t BOFF> __device__ __forceinline__ void wgmma_deep(float (&d)[64], uint32_t ub) {
    asm volatile(
        DESC_PRE DESC_B("%65", "%66") "mov.b64 da, %64;\n"
        "wgmma.mma_async.sync.aligned.m64n128k16.f32.bf16.bf16 "
        "{%0,%1,%2,%3,%4,%5,%6,%7,%8,%9,%10,%11,%12,%13,%14,%15,%16,%17,%18,%19,%20,%21,%22,%23,%24,%25,%26,%27,%28,%29,%30,%31,"
        "%32,%33,%34,%35,%36,%37,%38,%39,%40,%41,%42,%43,%44,%45,%46,%47,%48,%49,%50,%51,%52,%53,%54,%55,%56,%57,%58,%59,%60,%61,%62,%63}, "
        "da, db, %67, 1, 1, 0, 1;\n}\n"
        : F8(d, 0), F8(d, 8), F8(d, 16), F8(d, 24), F8(d, 32), F8(d, 40), F8(d, 48), F8(d, 56)
        : "n"(cdesc(AOFF, 16)), "r"(ub), "n"((uint32_t)cdesc(BOFF, 4096)), "n"(SC));
}
template <int SC, uint32_t AOFF, uint32_t BOFF> __device__ __forceinline__ void wgmma_x40(float (&d)[20], uint32_t ub) {
    asm volatile(
        DESC_PRE DESC_B("%21", "%22") "mov.b64 da, %20;\n"
        "wgmma.mma_async.sync.aligned.m64n40k16.f32.bf16.bf16 "
        "{%0,%1,%2,%3,%4,%5,%6,%7,%8,%9,%10,%11,%12,%13,%14,%15,%16,%17,%18,%19}, da, db, %23, 1, 1, 0, 0;\n}\n"
        : F8(d, 0), F8(d, 8), F4(d, 16)
        : "n"(cdesc(AOFF, 16)), "r"(ub), "n"((uint32_t)cdesc(BOFF, 16)), "n"(SC));
}
template <int SC, uint32_t AOFF, uint32_t BOFF> __device__ __forceinline__ void wgmma_x32(float (&d)[16], uint32_t ub) {
    asm volatile(
        DESC_PRE DESC_B("%17", "%18") "mov.b64 da, %16;\n"
        "wgmma.mma_async.sync.aligned.m64n32k16.f32.bf16.bf16 "
        "{%0,%1,%2,%3,%4,%5,%6,%7,%8,%9,%10,%11,%12,%13,%14,%15}, da, db, %19, 1, 1, 0, 0;\n}\n"
        : F8(d, 0), F8(d, 8)
        : "n"(cdesc(AOFF, 16)), "r"(ub), "n"((uint32_t)cdesc(BOFF, 16)), "n"(SC));
}
template <int SC, uint32_t BOFF> __device__ __forceinline__ void wgmma_sp(float (&d)[16], uint32_t a0, uint32_t a1, uint32_t a2, uint32_t a3, uint32_t ub, uint32_t meta) {
    asm volatile(
        DESC_PRE DESC_B("%20", "%21")
        "wgmma.mma_async.sp.sync.aligned.m64n32k32.f32.bf16.bf16 "
        "{%0,%1,%2,%3,%4,%5,%6,%7,%8,%9,%10,%11,%12,%13,%14,%15}, {%16,%17,%18,%19}, db, %22, 0, %23, 1, 1, 0;\n}\n"
        : F8(d, 0), F8(d, 8)
        : "r"(a0), "r"(a1), "r"(a2), "r"(a3), "r"(ub), "n"((uint32_t)cdesc(BOFF, 16)), "r"(meta), "n"(SC));
}
__device__ __forceinline__ void mma16816(float (&d)[4], uint32_t a0, uint32_t a2, uint32_t b0, uint32_t b1) {
    asm volatile("mma.sync.aligned.m16n8k16.row.col.f32.bf16.bf16.f32 {%0,%1,%2,%3}, {%4,%5,%6,%7}, {%8,%9}, {%0,%1,%2,%3};"
                 : "+f"(d[0]), "+f"(d[1]), "+f"(d[2]), "+f"(d[3])
                 : "r"(a0), "r"(0u), "r"(a2), "r"(0u), "r"(b0), "r"(b1));
}

__device__ __forceinline__ float gelu_exact(float x) {
    float u = 0.7978845608028654f * (x + 0.044715f * x * x * x);
    return __fdividef(x, 1.0f + __expf(-2.0f * u));
}
__device__ __forceinline__ float gelu_tanh(float x) {
    float u = x * fmaf(x * x, 0.7978845608028654f * 0.044715f, 0.7978845608028654f);
    float t;
    asm("tanh.approx.f32 %0, %1;" : "=f"(t) : "f"(u));
    float hx = 0.5f * x;
    return fmaf(hx, t, hx);
}
__device__ __forceinline__ float rbf(float x) { return bf_lo(pack_bf16(x, 0.f)); }

__device__ __forceinline__ void wt_item(uint8_t* dst, const uint4& v0, const uint4& v1, int o, int dh, int lane) {
    const uint32_t a[4] = {v0.x, v0.y, v0.z, v0.w}, b[4] = {v1.x, v1.y, v1.z, v1.w};
    uint8_t* base = dst + dh * 10240 + (40 * (o >> 2) + 8 * (o & 3)) * 128 + (lane & 3) * 4;
#pragma unroll
    for (int x = 0; x < 8; x++) {
        uint32_t w = __byte_perm(a[x >> 1], b[x >> 1], (x & 1) ? 0x7632 : 0x5410);
        uint8_t* p = base + x * 128 + (((lane >> 2) ^ x) << 4);
        *reinterpret_cast<uint32_t*>(p) = w;
        if ((o & 3) == 0) *reinterpret_cast<uint32_t*>(p + 32 * 128) = (x < 6) ? w : 0x3F803F80u;
    }
}

__device__ __forceinline__ void rotate16(uint32_t (&x)[16][2], bool p1, bool p2) {
#pragma unroll
    for (int r = 0; r < 2; r++) {
        uint32_t t[16];
#pragma unroll
        for (int i = 0; i < 16; i++) t[i] = p1 ? x[(i + 15) & 15][r] : x[i][r];
#pragma unroll
        for (int i = 0; i < 16; i++) x[i][r] = p2 ? t[(i + 14) & 15] : t[i];
    }
}

template <int K, int NA>
__device__ __forceinline__ void x_store(const float (&xa)[NA], uint32_t (&X)[3][16][2], uint32_t (&X3)[4][2]) {
#pragma unroll
    for (int t = 0; t < 4; t++)
#pragma unroll
        for (int r = 0; r < 2; r++) {
            uint32_t w = pack_bf16(xa[4 * t + r], xa[4 * t + 2 + r]);
            if (K == 12) X3[t][r] = w;
            else X[(K >> 2) % 3][4 * t + (K & 3)][r] = w;
        }
}

template <int I> struct IC { static constexpr int v = I; };
template <int B, int E, class Fn> __device__ __forceinline__ void static_for(Fn&& f) {
    if constexpr (B < E) {
        f(IC<B>{});
        static_for<B + 1, E>(f);
    }
}

__global__ void __cluster_dims__(2, 1, 1) __launch_bounds__(NTHREADS, 1)
fibinet_kernel(const __grid_constant__ CUtensorMap tmW1, const int* __restrict__ idx, const uint8_t* __restrict__ table,
               const unsigned short* __restrict__ se_w1, const unsigned short* __restrict__ se_w2,
               const uint8_t* __restrict__ w_bi, const uint8_t* __restrict__ w_cross,
               const unsigned short* __restrict__ w_deep2, __nv_bfloat16* __restrict__ out) {
    extern __shared__ __align__(1024) uint8_t smem_raw[];
    const int tid = threadIdx.x, lane = tid & 31;
    const int warp = uni(tid >> 5);
    const int cta = blockIdx.x, rank = cta & 1;
    uint32_t sb = smem_u32(smem_raw);
    asm volatile("mov.u32 %0, %0;" : "+r"(sb));
    if ((sb & 0x3FFFFu) != SBASE) __trap();
    uint8_t* sptr = smem_raw;
    const uint32_t bar = sb + OFF_BAR;

    const int* myidx = idx;
    int id0 = 0, id1 = 0, id2 = 0;
    if (warp >= 9) {
        if (warp < 11) {
            const int rho = (warp - 9) * 32 + lane;
            myidx = idx + ((cta >> 1) * 64 + ((rho >> 3) & 1) * 32 + (rho >> 4) * 8 + (rho & 7)) * 26 + 13 * rank;
        } else {
            myidx = idx + (cta * 32 + lane) * 26 + 13 * (1 - rank);
        }
        id0 = __ldg(myidx);
        id1 = __ldg(myidx + 1);
        id2 = __ldg(myidx + 2);
    }
    if (tid < NBAR) {
        uint32_t cnt;
        if (tid < B_WEMPTY) cnt = 1;
        else if (tid < B_DFULL) cnt = 8;
        else if (tid < B_DDONE) cnt = 64;
        else if (tid < B_XFULL) cnt = 8;
        else if (tid < B_XDONE) cnt = 32;
        else if (tid < B_YFULL) cnt = 8;
        else if (tid < B_YDONE) cnt = 64;
        else if (tid < B_GFULL) cnt = 8;
        else if (tid < B_GEMPTY) cnt = 1;
        else if (tid < B_WT1) cnt = 4;
        else if (tid == B_WT1 || tid == B_XCHF) cnt = 1;
        else cnt = 8;
        mbar_init(bar + tid * 8, cnt);
        if (tid == B_XCHF) asm volatile("mbarrier.arrive.expect_tx.shared::cta.b64 _, [%0], 32768;" ::"r"(bar + tid * 8) : "memory");
        asm volatile("fence.mbarrier_init.release.cluster;" ::: "memory");
    }
    fence_async();
    __syncthreads();
    asm volatile("barrier.cluster.arrive.release.aligned;" ::: "memory");

    if (warp >= 8) {
        asm volatile("setmaxnreg.dec.sync.aligned.u32 40;");
        if (warp == 8) {
            const int krow0 = rank * 13 * 128;
#pragma unroll 1
            for (int n = 0; n < 52; n++) {
                const int s = n & 3;
                if (n >= 4) mbar_wait(bar + (B_WEMPTY + s) * 8, ((n >> 2) - 1) & 1);
                tma3d_elect(sb + OFF_WR + s * 16384, &tmW1, krow0 + n * 32, bar + (B_WFULL + s) * 8);
            }
            {
                uint32_t target;
                asm volatile("ld.volatile.shared.u32 %0, [%1];" : "=r"(target) : "r"(bar + NBAR * 8) : "memory");
                asm volatile(
                    "{\n.reg .pred p;\n.reg .u32 c, v;\n.reg .s32 d;\nmov.u32 c, 0;\n"
                    "LW:\nld.acquire.gpu.global.u32 v, [%0];\nsub.s32 d, v, %1;\nsetp.ge.s32 p, d, 0;\n@p bra LD;\n"
                    "add.u32 c, c, 1;\nsetp.lt.u32 p, c, 1000000;\n@p bra LW;\ntrap;\nLD:\n}\n" ::"l"(&g_ready), "r"(target) : "memory");
                asm volatile("fence.proxy.async;" ::: "memory");
            }
            mbar_wait(bar + (B_WEMPTY + 0) * 8, 0);
            mbar_wait(bar + (B_WEMPTY + 1) * 8, 0);
            const uint8_t* gsrc = reinterpret_cast<const uint8_t*>(g_G);
            int slot = 0, ph = 1;
#pragma unroll 1
            for (int n = 0; n < 64; n++) {
                if (n == 4) {
                    mbar_wait(bar + (B_XDONE + 12) * 8, 0);
                    bulk_elect(sb + OFF_WT, g_WT1, 20480, bar + B_WT1 * 8);
                    mbar_wait(bar + B_XCONS * 8, 0);
                }
                if (n >= (int)NGS) mbar_wait(bar + (B_GEMPTY + slot) * 8, ph);
                bulk_elect(sb + OFF_WR + slot * GSLOT, gsrc + n * GBYTES, GBYTES, bar + (B_GFULL + slot) * 8);
                if (++slot == (int)NGS) { slot = 0; ph ^= 1; }
            }
        } else {
            const int hi = lane >> 4, ch = lane & 7, dh = (lane >> 3) & 1;
            const uint8_t* src0 = table + (lane & 15) * 16;
            const bool g1 = warp < 11;
            const uint32_t rowoff = g1 ? (uint32_t)((warp - 9) * 4096 + hi * 128) : (uint32_t)((1 - rank) * 1024 + hi * 128);
            const uint32_t qs = g1 ? 1024u : 2048u;
#pragma unroll 1
            for (int k = 0; k < 13; k++) {
                const int cur = id0;
                id0 = id1;
                id1 = id2;
                if (k + 3 < 13) id2 = __ldg(myidx + k + 3);
                if (g1) { if (k >= 4) mbar_wait(bar + (B_XDONE + k - 4) * 8, 0); }
                else mbar_wait(bar + (B_DDONE + k) * 8, 0);
                const uint32_t base = sb + (dh ? OFF_R1 + (k & 3) * 8192 : OFF_E0 + k * 8192) + rowoff;
                const uint32_t sw = (uint32_t)(ch ^ hi ^ (2 * (k & 3))) << 4;
#pragma unroll
                for (int j = 0; j < 16; j++) {
                    const int id = __shfl_sync(0xffffffffu, cur, 2 * j + hi);
                    cpasync16(base + (j >> 2) * qs + (j & 3) * 256 + (sw ^ ((j & 3) << 5)), src0 + (size_t)id * 256);
                }
                cpasync_arrive(bar + ((g1 ? B_DFULL : B_XFULL) + k) * 8);
            }
            if (g1) {
                const int rho = (warp - 9) * 32 + lane;
                const int* p = idx + (cta * 32 + (rho >> 4) * 8 + (rho & 7)) * 26 + 13 * ((rho >> 3) & 1);
                const int q = lane >> 3;
                const uint8_t* src1 = table + 128 + ch * 16;
                id0 = __ldg(p);
                id1 = __ldg(p + 1);
#pragma unroll 1
                for (int k = 0; k < 9; k++) {
                    const int cur = id0;
                    id0 = id1;
                    if (k + 2 < 9) id1 = __ldg(p + k + 2);
                    mbar_wait(bar + (B_YDONE + k) * 8, 0);
                    const int slot = k < 4 ? 9 + k : k - 4;
                    const uint32_t base = sb + OFF_E0 + slot * 8192 + (warp - 9) * 4096 + q * 128;
                    const uint32_t sw = (uint32_t)(ch ^ q ^ (2 * (k & 3))) << 4;
#pragma unroll
                    for (int j = 0; j < 8; j++) {
                        const int id = __shfl_sync(0xffffffffu, cur, 4 * j + q);
                        cpasync16(base + j * 512 + (sw ^ ((j & 1) << 6)), src1 + (size_t)id * 256);
                    }
                    cpasync_arrive(bar + (B_YFULL + k) * 8);
                }
            }
            asm volatile("cp.async.wait_all;" ::: "memory");
        }
        asm volatile("barrier.cluster.wait.acquire.aligned;" ::: "memory");
    } else {
        asm volatile("setmaxnreg.inc.sync.aligned.u32 232;");
        const int wg = warp >> 2, w = warp & 3, g = lane >> 2, c = lane & 3;

        {
            const uint8_t* wp = w_bi + (2 * lane) * 256 + warp * 16;
            const uint4 a0 = ldg128(wp), a1 = ldg128(wp + 256), b0 = ldg128(wp + 64 * 256), b1 = ldg128(wp + 65 * 256);
            const unsigned short w2v = __ldg(w_deep2 + tid);
            if (warp == 0) {
                const int pq = cta >> 6, oct = (cta >> 2) & 15, s = cta & 3;
                const int j = lane < 24 ? (4 * (lane >> 3) + ((lane >> 1) & 3) + 13 * (lane & 1)) : (lane == 24 ? 12 : 25);
                const bool valid = lane < 27 && lane != 25;
                uint4 L[4], H[4];
#pragma unroll
                for (int u = 0; u < 4; u++) {
                    L[u] = make_uint4(0, 0, 0, 0);
                    H[u] = L[u];
                    if (valid && (4 * s + u) < 13) {
                        const uint8_t* p = w_cross + ((size_t)(pq * 676 + (4 * s + u) * 26 + j) * 128 + oct * 8) * 2;
                        L[u] = ldg128(p);
                        H[u] = ldg128(p + 13 * 26 * 256);
                    }
                }
                const int R = 27 * pq + lane;
                uint8_t* dst = reinterpret_cast<uint8_t*>(g_G) + (size_t)((oct >> 3) * 32 + (oct & 3) * 8 + ((oct >> 2) & 1)) * GBYTES + R * 128;
                if (lane < 27) {
#pragma unroll
                    for (int kap = 0; kap < 4; kap++) {
                        uint32_t e[4][2];
#pragma unroll
                        for (int cc = 0; cc < 4; cc++) {
                            const int u = (kap - cc) & 3;
                            const uint32_t l = kap == 0 ? L[u].x : kap == 1 ? L[u].y : kap == 2 ? L[u].z : L[u].w;
                            const uint32_t h = kap == 0 ? H[u].x : kap == 1 ? H[u].y : kap == 2 ? H[u].z : H[u].w;
                            e[cc][0] = __byte_perm(l, h, 0x5410);
                            e[cc][1] = __byte_perm(l, h, 0x7632);
                        }
                        uint8_t* d2 = dst + kap * 2 * GBYTES;
                        *reinterpret_cast<uint4*>(d2 + (((2 * s) ^ (R & 7)) << 4)) = make_uint4(e[0][0], e[0][1], e[1][0], e[1][1]);
                        *reinterpret_cast<uint4*>(d2 + (((2 * s + 1) ^ (R & 7)) << 4)) = make_uint4(e[2][0], e[2][1], e[3][0], e[3][1]);
                    }
                }
                __threadfence();
            } else if (warp == 1) {
                uint32_t f[16];
#pragma unroll
                for (int nt = 0; nt < 2; nt++)
#pragma unroll
                    for (int s = 0; s < 4; s++) {
                        const int k = 4 * s + 3 - c, n = 8 * nt + g;
                        uint32_t v = 0;
                        if (k < 13 && n < 13) v = (uint32_t)__ldg(se_w1 + k * 13 + n) | ((uint32_t)__ldg(se_w1 + (13 + k) * 13 + n) << 16);
                        f[nt * 4 + s] = v;
                    }
#pragma unroll
                for (int s = 0; s < 4; s++)
#pragma unroll
                    for (int hh = 0; hh < 2; hh++) {
                        const int k = 4 * s + (g >> 1), fld = k + 13 * (g & 1), m = 8 * hh + 2 * c;
                        uint32_t v = 0;
                        if (k < 13 && m < 13) v = (uint32_t)__ldg(se_w2 + m * 26 + fld);
                        if (k < 13 && m + 1 < 13) v |= (uint32_t)__ldg(se_w2 + (m + 1) * 26 + fld) << 16;
                        f[8 + s * 2 + hh] = v;
                    }
#pragma unroll
                for (int q = 0; q < 4; q++)
                    *reinterpret_cast<uint4*>(sptr + OFF_SE + q * 512 + lane * 16) = make_uint4(f[4 * q], f[4 * q + 1], f[4 * q + 2], f[4 * q + 3]);
            } else if (warp == 2 && cta < 16) {
                const int o = cta & 7, dh = cta >> 3;
                const uint8_t* p = w_bi + (64 * dh + 2 * lane) * 256 + 128 + o * 16;
                const uint4 v0 = ldg128(p), v1 = ldg128(p + 256);
                wt_item(reinterpret_cast<uint8_t*>(g_WT1), v0, v1, o, dh, lane);
                __threadfence();
            }
            wt_item(sptr + OFF_WT, a0, a1, warp, 0, lane);
            wt_item(sptr + OFF_WT, b0, b1, warp, 1, lane);
            reinterpret_cast<float*>(sptr + OFF_W2)[tid] = __uint_as_float((uint32_t)w2v << 16);
            fence_async();
            asm volatile("bar.sync 1, 256;" ::: "memory");
            if (tid == 0) {
                asm volatile("fence.proxy.async;" ::: "memory");
                __threadfence();
                const unsigned int old = atomicAdd(&g_ready, 1u);
                asm volatile("st.volatile.shared.u32 [%0], %1;" ::"r"(bar + NBAR * 8), "r"((old & ~(unsigned)(NCTA - 1)) + NCTA) : "memory");
            }
            __syncwarp();
        }
        DBG_T(0);

        const uint32_t uWR = uni(wg * (8192 >> 4)), uWT = uni(wg * (40 * 128 >> 4));
        const bool p1 = (c & 1) != 0, p2 = (c & 2) != 0;

        uint32_t X[3][16][2], X3[4][2], Z[4] = {0u, 0u, 0u, 0u};
        float deep_logit;
        {
            float dacc[64];
            float xa[20];
            auto x_finish = [&](auto kc) {
                constexpr int K = decltype(kc)::v;
                reg_fence(xa);
                mbar_arrive_elect(bar + (B_XDONE + K) * 8);
                x_store<K>(xa, X, X3);
                const uint32_t zw = pack_bf16(xa[16] * (1.0f / 128.0f), xa[18] * (1.0f / 128.0f));
                Z[K >> 2] = (c == 3 - (K & 3)) ? zw : Z[K >> 2];
                if ((K & 3) == 3) rotate16(X[(K >> 2) % 3], p1, p2);
            };
            auto x_issue = [&](auto kc) {
                constexpr int K = decltype(kc)::v;
                mbar_wait(bar + (B_XFULL + K) * 8, 0);
                fence_async();
                wg_fence();
                static_for<0, 8>([&](auto jc) {
                    constexpr int J = decltype(jc)::v;
                    constexpr uint32_t AO = (J < 4 ? OFF_E0 + K * 8192 : OFF_R1 + (K & 3) * 8192) + (((J & 3) ^ (K & 3)) * 32);
                    constexpr uint32_t BO = OFF_WT + (J >> 2) * 10240 + (K & 3) * 256 + (J & 3) * 32;
                    wgmma_x40<(J > 0), AO, BO>(xa, uWT);
                });
                wg_commit();
            };
            static_for<0, 13>([&](auto kc) {
                constexpr int K = decltype(kc)::v;
                mbar_wait(bar + (B_DFULL + K) * 8, 0);
                fence_async();
                if (K == 0) DBG_T(1);
                static_for<0, 4>([&](auto cc) {
                    constexpr int CH = decltype(cc)::v;
                    mbar_wait(bar + (B_WFULL + CH) * 8, K & 1);
                    wg_fence();
                    static_for<0, 2>([&](auto jc) {
                        constexpr int J = CH * 2 + decltype(jc)::v;
                        constexpr uint32_t AO = (J < 4 ? OFF_E0 + K * 8192 : OFF_R1 + (K & 3) * 8192) + (((J & 3) ^ (K & 3)) * 32);
                        constexpr uint32_t BO = OFF_WR + CH * 16384 + (J & 1) * 2048;
                        wgmma_deep<(K + J > 0), AO, BO>(dacc, uWR);
                    });
                    wg_commit();
                    if constexpr (CH > 0) {
                        wg_wait<1>();
                        mbar_arrive_elect(bar + (B_WEMPTY + CH - 1) * 8);
                    } else if constexpr (K >= 2) {
                        wg_wait<1>();
                        x_finish(IC<K - 2>{});
                    } else if constexpr (K == 1) {
                        wg_wait<1>();
                        mbar_arrive_elect(bar + (B_WEMPTY + 3) * 8);
                        mbar_arrive_elect(bar + (B_DDONE + 0) * 8);
                    }
                });
                if constexpr (K >= 1) {
                    x_issue(IC<K - 1>{});
                    wg_wait<1>();
                    mbar_arrive_elect(bar + (B_WEMPTY + 3) * 8);
                    mbar_arrive_elect(bar + (B_DDONE + K) * 8);
                }
            });
            DBG_T(2);
            reg_fence(dacc);
            asm volatile("barrier.cluster.wait.acquire.aligned;" ::: "memory");
            uint32_t rbar, rbuf;
            asm volatile("mapa.shared::cluster.u32 %0, %1, %2;" : "=r"(rbar) : "r"(bar), "r"(rank ^ 1));
            asm volatile("mapa.shared::cluster.u32 %0, %1, %2;" : "=r"(rbuf) : "r"(sb + OFF_XCH + tid * 16), "r"(rank ^ 1));
            mbar_arrive_remote_elect(rbar + B_CANSEND * 8);
            wg_wait<0>();
            x_finish(IC<11>{});
            mbar_wait_cluster(bar + B_CANSEND * 8, 0);
            float keep[32];
#pragma unroll
            for (int j = 0; j < 8; j++) {
                float s[4];
#pragma unroll
                for (int x = 0; x < 4; x++) {
                    const int i0 = 8 * j + 4 * (x >> 1) + (x & 1);
                    s[x] = rank ? dacc[i0] : dacc[i0 + 2];
                    keep[4 * j + x] = rank ? dacc[i0 + 2] : dacc[i0];
                }
                asm volatile("st.async.shared::cluster.mbarrier::complete_tx::bytes.v4.f32 [%0], {%1,%2,%3,%4}, [%5];" ::"r"(rbuf + j * 4096),
                             "f"(s[0]), "f"(s[1]), "f"(s[2]), "f"(s[3]), "r"(rbar + B_XCHF * 8) : "memory");
            }
            x_issue(IC<12>{});
            mbar_wait_cluster(bar + B_XCHF * 8, 0);
            float dl0 = 0.f, dl1 = 0.f;
#pragma unroll
            for (int j = 0; j < 8; j++) {
                const uint4 v = lds128(sb + OFF_XCH + tid * 16 + j * 4096);
                const float2 wa = *reinterpret_cast<const float2*>(sptr + OFF_W2 + (wg * 128 + 16 * j + 2 * c) * 4);
                const float2 wb = *reinterpret_cast<const float2*>(sptr + OFF_W2 + (wg * 128 + 16 * j + 8 + 2 * c) * 4);
                dl0 = fmaf(gelu_tanh(keep[4 * j + 0] + __uint_as_float(v.x)), wa.x, dl0);
                dl1 = fmaf(gelu_tanh(keep[4 * j + 1] + __uint_as_float(v.y)), wa.y, dl1);
                dl0 = fmaf(gelu_tanh(keep[4 * j + 2] + __uint_as_float(v.z)), wb.x, dl0);
                dl1 = fmaf(gelu_tanh(keep[4 * j + 3] + __uint_as_float(v.w)), wb.y, dl1);
            }
            fence_async();
            __syncwarp();
            mbar_arrive_elect(bar + B_XCONS * 8);
            deep_logit = dl0 + dl1;
            wg_wait<0>();
            x_finish(IC<12>{});
        }
        DBG_T(3);

        uint32_t aw[3][4], aw3, own[3];
        {
            const uint4 f0 = lds128(sb + OFF_SE + lane * 16), f1 = lds128(sb + OFF_SE + 512 + lane * 16);
            const uint4 f2 = lds128(sb + OFF_SE + 1024 + lane * 16), f3 = lds128(sb + OFF_SE + 1536 + lane * 16);
            float h0[4] = {0.f, 0.f, 0.f, 0.f}, h1[4] = {0.f, 0.f, 0.f, 0.f};
            mma16816(h0, Z[0], Z[1], f0.x, f0.y);
            mma16816(h1, Z[0], Z[1], f1.x, f1.y);
            mma16816(h0, Z[2], Z[3], f0.z, f0.w);
            mma16816(h1, Z[2], Z[3], f1.z, f1.w);
            const uint32_t ha = pack_bf16(gelu_exact(rbf(h0[0])), gelu_exact(rbf(h0[1])));
            const uint32_t hb = pack_bf16(gelu_exact(rbf(h1[0])), gelu_exact(rbf(h1[1])));
            float o[4][4];
#pragma unroll
            for (int s = 0; s < 4; s++) o[s][0] = o[s][1] = o[s][2] = o[s][3] = 0.f;
            mma16816(o[0], ha, hb, f2.x, f2.y);
            mma16816(o[1], ha, hb, f2.z, f2.w);
            mma16816(o[2], ha, hb, f3.x, f3.y);
            mma16816(o[3], ha, hb, f3.z, f3.w);
            uint32_t ow[4];
#pragma unroll
            for (int s = 0; s < 4; s++)
                ow[s] = pack_bf16(__fdividef(1.0f, 1.0f + __expf(-rbf(o[s][0]))), __fdividef(1.0f, 1.0f + __expf(-rbf(o[s][1]))));
#pragma unroll
            for (int s = 0; s < 3; s++) {
                own[s] = ow[s];
#pragma unroll
                for (int kap = 0; kap < 4; kap++) aw[s][kap] = __shfl_sync(0xffffffffu, ow[s], (lane & ~3) | ((kap - c) & 3));
            }
            aw3 = __shfl_sync(0xffffffffu, ow[3], lane & ~3);
        }
        DBG_T(4);

        float accp[3] = {0.f, 0.f, 0.f}, accq[7] = {0.f, 0.f, 0.f, 0.f, 0.f, 0.f, 0.f};
        uint32_t meta = 0xEEEE4444u;
        asm volatile("mov.u32 %0, %0;" : "+r"(meta));
        int gslot = uni(wg), gph = 0;
        const uint32_t erow = sb + w * 2048 + g * 128;
        uint32_t eb[4];
#pragma unroll
        for (int t = 0; t < 3; t++) eb[t] = erow + OFF_E0 + (4 * t + c) * 8192;
        eb[3] = erow + OFF_E0 + 12 * 8192 + (c & 1) * 1024;

#pragma unroll 1
        for (int eta = 0; eta < 2; eta++) {
            if (eta == 1) {
                float xb[2][16];
                const uint32_t uWT1 = uni(wg * (40 * 128 >> 4));
                mbar_wait(bar + B_WT1 * 8, 0);
                static_for<0, 14>([&](auto nc) {
                    constexpr int N = decltype(nc)::v;
                    if constexpr (N < 13) {
                        constexpr int K = N < 4 ? 9 + N : N - 4;
                        constexpr int SL = N < 8 ? 5 + N : N - 8;
                        if constexpr (N >= 4) {
                            mbar_wait(bar + (B_YFULL + N - 4) * 8, 0);
                            fence_async();
                        }
                        wg_fence();
                        static_for<0, 8>([&](auto jc) {
                            constexpr int J = decltype(jc)::v;
                            constexpr uint32_t AO = (J < 4 ? OFF_E0 + K * 8192 : (N < 4 ? OFF_R1 + (K & 3) * 8192 : OFF_E0 + SL * 8192)) + (((J & 3) ^ (K & 3)) * 32);
                            constexpr uint32_t BO = OFF_WT + (J >> 2) * 10240 + (K & 3) * 256 + (J & 3) * 32;
                            wgmma_x32<(J > 0), AO, BO>(xb[N & 1], uWT1);
                        });
                        wg_commit();
                    }
                    if constexpr (N >= 1) {
                        constexpr int P = N - 1;
                        constexpr int K = P < 4 ? 9 + P : P - 4;
                        if constexpr (N < 13) wg_wait<1>(); else wg_wait<0>();
                        reg_fence(xb[P & 1]);
                        if constexpr (P < 9) mbar_arrive_elect(bar + (B_YDONE + P) * 8);
                        x_store<K>(xb[P & 1], X, X3);
                        if constexpr (K == 3 || K == 7 || K == 8) rotate16(X[K >> 2], p1, p2);
                    }
                });
                eb[0] = erow + OFF_E0 + (9 + c) * 8192;
                eb[1] = erow + OFF_E0 + c * 8192;
                eb[2] = erow + (c == 0 ? OFF_E0 + 4 * 8192 : OFF_R1 + c * 8192);
                eb[3] = erow + OFF_R1 + (c & 1) * 1024;
                DBG_T(6);
            }
            float P[16], Q[16];
            static_for<0, 4>([&](auto tc) {
                constexpr int T = decltype(tc)::v;
                uint4 ev[7];
                const uint32_t sw = (uint32_t)((4 * wg + T) ^ g);
#pragma unroll
                for (int t = 0; t < 3; t++) {
                    ev[2 * t] = lds128(eb[t] + ((sw ^ (2 * c)) << 4));
                    ev[2 * t + 1] = lds128(eb[t] + 1024 + ((sw ^ (2 * c)) << 4));
                }
                ev[6] = lds128(eb[3] + (sw << 4));
                static_for<0, 4>([&](auto kc) {
                    constexpr int KA = decltype(kc)::v;
                    constexpr int PI = 4 * T + KA;
                    const uint32_t q0 = hmul2(X[0][PI][0], aw[0][KA]), q1 = hmul2(X[0][PI][1], aw[0][KA]);
                    const uint32_t q2 = hmul2(X[1][PI][0], aw[1][KA]), q3 = hmul2(X[1][PI][1], aw[1][KA]);
                    const uint32_t q4 = hmul2(X[2][PI][0], aw[2][KA]), q5 = hmul2(X[2][PI][1], aw[2][KA]);
                    const uint32_t q6 = hmul2(X3[T][0], aw3), q7 = hmul2(X3[T][1], aw3);
                    const uint32_t m0 = vmov(X[2][PI][0]), m1 = vmov(X[2][PI][1]), m2 = vmov(X3[T][0]), m3 = vmov(X3[T][1]);
                    const uint32_t db = gslot * (GSLOT >> 4);
                    mbar_wait(bar + (B_GFULL + gslot) * 8, gph);
                    wg_fence();
                    wgmma_sp<0, OFF_WR>(P, X[0][PI][0], X[0][PI][1], X[1][PI][0], X[1][PI][1], db, meta);
                    wgmma_sp<0, OFF_WR + 3456>(Q, q0, q1, q2, q3, db, meta);
                    wgmma_sp<1, OFF_WR + 64>(P, m0, m1, m2, m3, db, meta);
                    wgmma_sp<1, OFF_WR + 3456 + 64>(Q, q4, q5, q6, q7, db, meta);
                    wg_commit();
                    wg_wait<0>();
                    reg_fence(P);
                    reg_fence(Q);
                    mbar_arrive_elect(bar + (B_GEMPTY + gslot) * 8);
                    gslot += 2;
                    if (gslot >= (int)NGS) { gslot -= NGS; gph ^= 1; }
#pragma unroll
                    for (int sl = 0; sl < 7; sl++) {
                        const uint32_t wd = KA == 0 ? ev[sl].x : KA == 1 ? ev[sl].y : KA == 2 ? ev[sl].z : ev[sl].w;
                        const float e0 = bf_lo(wd), e1 = bf_hi(wd);
                        const int i0 = 4 * (sl >> 1) + (sl & 1);
                        const int pi = sl == 6 ? 2 : (sl & 1);
                        accp[pi] = fmaf(e0, P[i0], accp[pi]);
                        accq[sl] = fmaf(e0, Q[i0], accq[sl]);
                        accp[pi] = fmaf(e1, P[i0 + 2], accp[pi]);
                        accq[sl] = fmaf(e1, Q[i0 + 2], accq[sl]);
                    }
                });
            });
            if (eta == 0) DBG_T(5);
        }
        DBG_T(7);

        float cr = accp[0] + accp[1];
#pragma unroll
        for (int t = 0; t < 3; t++) cr = fmaf(bf_hi(own[t]), accq[2 * t + 1], fmaf(bf_lo(own[t]), accq[2 * t], cr));
        const float last = fmaf(p1 ? bf_hi(aw3) : bf_lo(aw3), accq[6], accp[2]);
        cr += p2 ? 0.f : last;
        cr += __shfl_xor_sync(0xffffffffu, cr, 1);
        cr += __shfl_xor_sync(0xffffffffu, cr, 2);
        deep_logit += __shfl_xor_sync(0xffffffffu, deep_logit, 1);
        deep_logit += __shfl_xor_sync(0xffffffffu, deep_logit, 2);
        float2* res = reinterpret_cast<float2*>(sptr + OFF_RES);
        if (c == 0) res[wg * 32 + w * 8 + g] = make_float2(cr, deep_logit);
        asm volatile("bar.sync 1, 256;" ::: "memory");
        if (tid < 32) {
            const float2 r0 = res[tid], r1 = res[32 + tid];
            out[cta * 32 + tid] = __float2bfloat16(rbf(r0.x + r1.x) + rbf(r0.y + r1.y));
        }
        DBG_T(8);
    }
}

typedef CUresult (*PFN_encodeTiled)(CUtensorMap*, CUtensorMapDataType, cuuint32_t, void*, const cuuint64_t*, const cuuint64_t*,
                                    const cuuint32_t*, const cuuint32_t*, CUtensorMapInterleave, CUtensorMapSwizzle,
                                    CUtensorMapL2promotion, CUtensorMapFloatOOBfill);

}

extern "C" void kernel_launch(void* const* d_in, const int* in_sizes, int n_in, void* d_out, int out_size) {
    (void)in_sizes; (void)n_in; (void)out_size;
    static PFN_encodeTiled enc = nullptr;
    if (!enc) {
        void* fn = nullptr;
        cudaDriverEntryPointQueryResult st;
        cudaGetDriverEntryPoint("cuTensorMapEncodeTiled", &fn, cudaEnableDefault, &st);
        enc = (PFN_encodeTiled)fn;
        cudaFuncSetAttribute(fibinet_kernel, cudaFuncAttributeMaxDynamicSharedMemorySize, SMEM_BYTES);
    }
    CUtensorMap tm;
    const cuuint64_t dims[3] = {64, 3328, 4};
    const cuuint64_t strides[2] = {512, 128};
    const cuuint32_t box[3] = {64, 32, 4};
    const cuuint32_t estr[3] = {1, 1, 1};
    enc(&tm, CU_TENSOR_MAP_DATA_TYPE_BFLOAT16, 3, d_in[6], dims, strides, box, estr, CU_TENSOR_MAP_INTERLEAVE_NONE,
        CU_TENSOR_MAP_SWIZZLE_128B, CU_TENSOR_MAP_L2_PROMOTION_L2_256B, CU_TENSOR_MAP_FLOAT_OOB_FILL_NONE);
    fibinet_kernel<<<NCTA, NTHREADS, SMEM_BYTES>>>(tm, (const int*)d_in[0], (const uint8_t*)d_in[1], (const unsigned short*)d_in[2],
                                                  (const unsigned short*)d_in[3], (const uint8_t*)d_in[4], (const uint8_t*)d_in[5],
                                                  (const unsigned short*)d_in[7], (__nv_bfloat16*)d_out);
}
```

```cpp
#include <cuda_runtime.h>
#include <cuda_bf16.h>
#include <cuda.h>
#include <stdint.h>

namespace {

constexpr int NCTA = 128;
constexpr int NPREP = 4;
constexpr int NTHREADS = 384;
#define PD 3000
#define W1P 900
#define EL 1
#define G1O 600
#define G1P 1100
constexpr int W1_PACE = W1P;
constexpr int PREP_DELAY = PD;
constexpr int G1_PACE = G1P;

constexpr uint32_t OFF_E0 = 0;
constexpr uint32_t OFF_R1 = 13 * 8192;
constexpr uint32_t OFF_WR = OFF_R1 + 4 * 8192;
constexpr uint32_t OFF_WT = OFF_WR + 65536;
constexpr uint32_t OFF_SE = OFF_WT + 20480;
constexpr uint32_t OFF_RES = OFF_SE + 4096;
constexpr uint32_t OFF_BAR = OFF_RES + 512;
constexpr uint32_t OFF_IX2 = OFF_BAR + 768;
constexpr uint32_t OFF_IX1 = OFF_SE;
constexpr uint32_t OFF_W2 = OFF_SE + 2048;
constexpr uint32_t SMEM_USED = OFF_IX2 + 1664;
constexpr uint32_t SMEM_BYTES = SMEM_USED;

constexpr uint32_t GSLOT = 14336, GBYTES = 13824;
constexpr uint32_t OFF_G0 = OFF_R1;
constexpr uint32_t OFF_G1 = OFF_E0 + 65536;
constexpr int G1_WRAP = -(65536 + 4 * (int)GSLOT);
constexpr uint32_t OFF_WF = OFF_R1;
constexpr uint32_t OFF_E1 = OFF_R1 + 16384;
constexpr uint32_t OFF_XCH = OFF_WR + 4 * 8192;
constexpr uint32_t OFF_WTMP = OFF_WT;
constexpr uint32_t OFF_WS1 = OFF_E0 + 4 * 8192;
constexpr uint32_t OFF_X12 = OFF_WR + 3 * 8192;

constexpr int B_GFULL = 0;
constexpr int B_YFULL = 8;
constexpr int B_GEMPTY = 16;
constexpr int B_WEMPTY = 32;
constexpr int B_HDONE = 40, B_DDONE = 44;
constexpr int B_LAST = 48;
constexpr int B_DFULL = 56, B_DH4 = 60;
constexpr int B_WFULL = 64;
constexpr int B_YDONE = 72, B_YD2 = 73, B_EPI = 74, B_WS1 = 75, B_CANSEND = 76;
constexpr int B_WF = 78, B_XCHF = 79, B_MISC = 80, B_DL = 81;
constexpr int B_XFULL = 24;
constexpr int B_XDONE = 52;

__device__ uint4 g_G[32 * GBYTES / 16];
__device__ uint4 g_WF[8 * 128];
__device__ uint4 g_MISC[3072 / 16];
__device__ unsigned int g_ready, g_epoch;
#define TR(i) do {} while (0)
#define TG(i) do {} while (0)
#define WT(i, x) x
#define TR6(i) do {} while (0)
#define TR3(i) do {} while (0)
#define TR2(i) do {} while (0)

__device__ __forceinline__ uint32_t smem_u32(const void* p) { return (uint32_t)__cvta_generic_to_shared(p); }

__device__ __forceinline__ void mbar_init(uint32_t b, uint32_t c) {
    asm volatile("mbarrier.init.shared::cta.b64 [%0], %1;" ::"r"(b), "r"(c) : "memory");
}
__device__ __forceinline__ void mbar_wait(uint32_t b, uint32_t ph) {
    asm volatile(
        "{\n.reg .pred p;\n.reg .u32 c;\nmov.u32 c, 0;\n"
        "LW:\nmbarrier.try_wait.parity.shared::cta.b64 p, [%0], %1;\n@p bra LD;\n"
        "add.u32 c, c, 1;\nsetp.lt.u32 p, c, 2000000;\n@p bra LW;\ntrap;\nLD:\n}\n" ::"r"(b), "r"(ph) : "memory");
}
__device__ __forceinline__ void mbar_sleep(uint32_t b, uint32_t ph) {
    asm volatile(
        "{\n.reg .pred p;\n.reg .u32 c;\nmov.u32 c, 0;\n"
        "LW:\nmbarrier.try_wait.parity.shared::cta.b64 p, [%0], %1, 20000;\n@p bra LD;\n"
        "add.u32 c, c, 1;\nsetp.lt.u32 p, c, 100000;\n@p bra LW;\ntrap;\nLD:\n}\n" ::"r"(b), "r"(ph) : "memory");
}
template <int PH> __device__ __forceinline__ void cwait(uint32_t b) {
    asm volatile("{\n.reg .pred p;\nLW:\nmbarrier.try_wait.parity.shared::cta.b64 p, [%0], %1;\n@!p bra LW;\n}\n" ::"r"(b), "n"(PH) : "memory");
}
__device__ __forceinline__ uint32_t probe(uint32_t b, uint32_t ph) {
    uint32_t r;
    asm volatile("{\n.reg .pred p;\nmbarrier.test_wait.parity.shared::cta.b64 p, [%1], %2;\nselp.u32 %0, 1, 0, p;\n}\n" : "=r"(r) : "r"(b), "r"(ph) : "memory");
    return r;
}
__device__ __forceinline__ void confirm(uint32_t ok, uint32_t b, uint32_t ph) {
    asm volatile("{\n.reg .pred p;\nsetp.ne.u32 p, %2, 0;\n@p bra LD;\nLW:\nmbarrier.try_wait.parity.shared::cta.b64 p, [%0], %1;\n@!p bra LW;\nLD:\n}\n"
                 ::"r"(b), "r"(ph), "r"(ok) : "memory");
}
__device__ __forceinline__ void arrive0(uint32_t b, uint32_t lane) {
    asm volatile("{\n.reg .pred p;\nsetp.eq.u32 p, %1, 0;\n@p mbarrier.arrive.shared::cta.b64 _, [%0];\n}\n" ::"r"(b), "r"(lane) : "memory");
}
__device__ __forceinline__ void arrive1(uint32_t b, uint32_t lane) {
    asm volatile("{\n.reg .pred p;\nsetp.eq.u32 p, %1, 1;\n@p mbarrier.arrive.shared::cta.b64 _, [%0];\n}\n" ::"r"(b), "r"(lane) : "memory");
}
__device__ __forceinline__ void mbar_wait_cluster(uint32_t b, uint32_t ph) {
    asm volatile(
        "{\n.reg .pred p;\n.reg .u32 c;\nmov.u32 c, 0;\n"
        "LW:\nmbarrier.try_wait.parity.acquire.cluster.shared::cta.b64 p, [%0], %1;\n@p bra LD;\n"
        "add.u32 c, c, 1;\nsetp.lt.u32 p, c, 2000000;\n@p bra LW;\ntrap;\nLD:\n}\n" ::"r"(b), "r"(ph) : "memory");
}
__device__ __forceinline__ void mbar_arrive_remote_elect(uint32_t rb) {
    asm volatile("{\n.reg .pred p;\nelect.sync _|p, 0xffffffff;\n@p mbarrier.arrive.relaxed.cluster.shared::cluster.b64 _, [%0];\n}\n" ::"r"(rb) : "memory");
}
__device__ __forceinline__ void cpasync_arrive(uint32_t b) {
    asm volatile("cp.async.mbarrier.arrive.noinc.shared::cta.b64 [%0];" ::"r"(b) : "memory");
}
__device__ __forceinline__ void cpasync16(uint32_t dst, const void* src) {
    asm volatile("cp.async.cg.shared.global [%0], [%1], 16;" ::"r"(dst), "l"(src) : "memory");
}
__device__ __forceinline__ void bulk_elect(uint32_t dst, const void* src, uint32_t bytes, uint32_t bar) {
    asm volatile(
        "{\n.reg .pred p;\nelect.sync _|p, 0xffffffff;\n"
        "@p mbarrier.arrive.expect_tx.shared::cta.b64 _, [%3], %2;\n"
        "@p cp.async.bulk.shared::cluster.global.mbarrier::complete_tx::bytes [%0], [%1], %2, [%3];\n}\n" ::"r"(dst), "l"(src), "r"(bytes), "r"(bar) : "memory");
}
__device__ __forceinline__ void tma3d_elect(uint32_t dst, const CUtensorMap* tm, int c1, uint32_t bar) {
    asm volatile(
        "{\n.reg .pred p;\nelect.sync _|p, 0xffffffff;\n"
        "@p mbarrier.arrive.expect_tx.shared::cta.b64 _, [%3], 8192;\n"
        "@p cp.async.bulk.tensor.3d.shared::cluster.global.mbarrier::complete_tx::bytes [%0], [%1, {0, %2, 0}], [%3];\n}\n" ::"r"(dst), "l"(tm), "r"(c1), "r"(bar) : "memory");
}
__device__ __forceinline__ uint32_t uni(uint32_t v) {
    uint32_t r;
    asm volatile("redux.sync.or.b32 %0, %1, 0xffffffff;" : "=r"(r) : "r"(v));
    return r;
}
__device__ __forceinline__ uint32_t vmov(uint32_t v, uint32_t z) {
    uint32_t r;
    asm volatile("or.b32 %0, %1, %2;" : "=r"(r) : "r"(v), "r"(z));
    return r;
}
template <int OFF> __device__ __forceinline__ int ldi(const int* p) {
    int v;
    asm volatile("ld.global.nc.u32 %0, [%1+%2];" : "=r"(v) : "l"(p), "n"(OFF * 4));
    return v;
}
__device__ __forceinline__ void fence_async() { asm volatile("fence.proxy.async.shared::cta;" ::: "memory"); }
__device__ __forceinline__ void fence_acq() { asm volatile("fence.proxy.async::generic.acquire.sync_restrict::shared::cluster.cluster;" ::: "memory"); }
__device__ __forceinline__ void wg_fence() { asm volatile("wgmma.fence.sync.aligned;" ::: "memory"); }
__device__ __forceinline__ void wg_commit() { asm volatile("wgmma.commit_group.sync.aligned;" ::: "memory"); }
template <int N> __device__ __forceinline__ void wg_wait() { asm volatile("wgmma.wait_group.sync.aligned %0;" ::"n"(N) : "memory"); }
template <int N> __device__ __forceinline__ void reg_fence(float (&d)[N]) {
#pragma unroll
    for (int i = 0; i < N; i++) asm volatile("" : "+f"(d[i])::"memory");
}
__device__ __forceinline__ uint32_t pack_bf16(float lo, float hi) {
    uint32_t r;
    asm("cvt.rn.bf16x2.f32 %0, %1, %2;" : "=r"(r) : "f"(hi), "f"(lo));
    return r;
}
__device__ __forceinline__ uint32_t vpack(float lo, float hi) {
    uint32_t r;
    asm volatile("cvt.rn.bf16x2.f32 %0, %1, %2;" : "=r"(r) : "f"(hi), "f"(lo));
    return r;
}
__device__ __forceinline__ float vadd(float a, float b) {
    float r;
    asm volatile("add.f32 %0, %1, %2;" : "=f"(r) : "f"(a), "f"(b));
    return r;
}
__device__ __forceinline__ float bf_lo(uint32_t w) { return __uint_as_float(w << 16); }
__device__ __forceinline__ float bf_hi(uint32_t w) { return __uint_as_float(w & 0xffff0000u); }
__device__ __forceinline__ uint32_t hmul2(uint32_t a, uint32_t b) {
    uint32_t r;
    asm("mul.rn.bf16x2 %0, %1, %2;" : "=r"(r) : "r"(a), "r"(b));
    return r;
}
__device__ __forceinline__ uint4 lds128(uint32_t a) {
    uint4 v;
    asm volatile("ld.shared.v4.u32 {%0,%1,%2,%3}, [%4];" : "=r"(v.x), "=r"(v.y), "=r"(v.z), "=r"(v.w) : "r"(a) : "memory");
    return v;
}

constexpr uint32_t SBASE = 1024;
constexpr uint32_t DESC_HI = (1024u >> 4) | (1u << 30);
__host__ __device__ constexpr uint64_t cdesc(uint32_t off, uint32_t lbo) { return ((uint64_t)DESC_HI << 32) | ((SBASE + off) >> 4) | ((lbo >> 4) << 16); }
#define DESC_B(reg, imm) "add.u32 lo, " reg ", " imm ";\nmov.b64 db, {lo, hi};\n"
#define DESC_A(reg, imm) "add.u32 lo, " reg ", " imm ";\nmov.b64 da, {lo, hi};\n"
#define DESC_PRE "{\n.reg .b32 lo, hi;\n.reg .b64 db, da;\nmov.b32 hi, 0x40000040;\n"

#define F8(d, o) "+f"(d[o + 0]), "+f"(d[o + 1]), "+f"(d[o + 2]), "+f"(d[o + 3]), "+f"(d[o + 4]), "+f"(d[o + 5]), "+f"(d[o + 6]), "+f"(d[o + 7])
#define F4(d, o) "+f"(d[o + 0]), "+f"(d[o + 1]), "+f"(d[o + 2]), "+f"(d[o + 3])

template <int SC, uint32_t AOFF, uint32_t BOFF> __device__ __forceinline__ void wgmma_deep(float (&d)[64], uint32_t ua, uint32_t ub) {
    asm volatile(
        DESC_PRE DESC_B("%65", "%66") DESC_A("%68", "%64")
        "wgmma.mma_async.sync.aligned.m64n128k16.f32.bf16.bf16 "
        "{%0,%1,%2,%3,%4,%5,%6,%7,%8,%9,%10,%11,%12,%13,%14,%15,%16,%17,%18,%19,%20,%21,%22,%23,%24,%25,%26,%27,%28,%29,%30,%31,"
        "%32,%33,%34,%35,%36,%37,%38,%39,%40,%41,%42,%43,%44,%45,%46,%47,%48,%49,%50,%51,%52,%53,%54,%55,%56,%57,%58,%59,%60,%61,%62,%63}, "
        "da, db, %67, 1, 1, 0, 1;\n}\n"
        : F8(d, 0), F8(d, 8), F8(d, 16), F8(d, 24), F8(d, 32), F8(d, 40), F8(d, 48), F8(d, 56)
        : "n"((uint32_t)cdesc(AOFF, 16)), "r"(ub), "n"((uint32_t)cdesc(BOFF, 2048)), "n"(SC), "r"(ua));
}
template <int SC, uint32_t AOFF, uint32_t BOFF> __device__ __forceinline__ void wgmma_x40(float (&d)[20], uint32_t ua, uint32_t ub) {
    asm volatile(
        DESC_PRE DESC_B("%21", "%22") DESC_A("%24", "%20")
        "wgmma.mma_async.sync.aligned.m64n40k16.f32.bf16.bf16 "
        "{%0,%1,%2,%3,%4,%5,%6,%7,%8,%9,%10,%11,%12,%13,%14,%15,%16,%17,%18,%19}, da, db, %23, 1, 1, 0, 0;\n}\n"
        : F8(d, 0), F8(d, 8), F4(d, 16)
        : "n"((uint32_t)cdesc(AOFF, 16)), "r"(ub), "n"((uint32_t)cdesc(BOFF, 16)), "n"(SC), "r"(ua));
}
template <int SC, uint32_t BOFF> __device__ __forceinline__ void wgmma_t64(float (&d)[32], const uint4& a, uint32_t ub) {
    asm volatile(
        DESC_PRE DESC_B("%36", "%37")
        "wgmma.mma_async.sync.aligned.m64n64k16.f32.bf16.bf16 "
        "{%0,%1,%2,%3,%4,%5,%6,%7,%8,%9,%10,%11,%12,%13,%14,%15,%16,%17,%18,%19,%20,%21,%22,%23,%24,%25,%26,%27,%28,%29,%30,%31}, "
        "{%32,%33,%34,%35}, db, %38, 1, 1, 0;\n}\n"
        : F8(d, 0), F8(d, 8), F8(d, 16), F8(d, 24)
        : "r"(a.x), "r"(a.y), "r"(a.z), "r"(a.w), "r"(ub), "n"((uint32_t)cdesc(BOFF, 16)), "n"(SC));
}
__device__ __forceinline__ void ldsm4t(uint32_t& r0, uint32_t& r1, uint32_t& r2, uint32_t& r3, uint32_t a) {
    asm volatile("ldmatrix.sync.aligned.m8n8.x4.trans.shared.b16 {%0,%1,%2,%3}, [%4];" : "=r"(r0), "=r"(r1), "=r"(r2), "=r"(r3) : "r"(a) : "memory");
}
__device__ __forceinline__ void stsm4(uint32_t a, uint32_t r0, uint32_t r1, uint32_t r2, uint32_t r3) {
    asm volatile("stmatrix.sync.aligned.m8n8.x4.shared.b16 [%0], {%1,%2,%3,%4};" ::"r"(a), "r"(r0), "r"(r1), "r"(r2), "r"(r3) : "memory");
}
template <int SC> __device__ __forceinline__ void wgmma_sp(float (&d)[16], uint32_t a0, uint32_t a1, uint32_t a2, uint32_t a3, uint64_t& db, uint32_t meta, uint32_t inc) {
    asm volatile(
        "{\n.reg .b32 lo, hi;\n"
        "wgmma.mma_async.sp.sync.aligned.m64n32k32.f32.bf16.bf16 "
        "{%0,%1,%2,%3,%4,%5,%6,%7,%8,%9,%10,%11,%12,%13,%14,%15}, {%17,%18,%19,%20}, %16, %21, 0, %22, 1, 1, 0;\n"
        "mov.b64 {lo, hi}, %16;\nadd.s32 lo, lo, %23;\nmov.b64 %16, {lo, hi};\n}\n"
        : F8(d, 0), F8(d, 8), "+l"(db)
        : "r"(a0), "r"(a1), "r"(a2), "r"(a3), "r"(meta), "n"(SC), "r"(inc));
}
__device__ __forceinline__ void mma16816(float (&d)[4], uint32_t a0, uint32_t a2, uint32_t b0, uint32_t b1) {
    asm volatile("mma.sync.aligned.m16n8k16.row.col.f32.bf16.bf16.f32 {%0,%1,%2,%3}, {%4,%5,%6,%7}, {%8,%9}, {%0,%1,%2,%3};"
                 : "+f"(d[0]), "+f"(d[1]), "+f"(d[2]), "+f"(d[3])
                 : "r"(a0), "r"(0u), "r"(a2), "r"(0u), "r"(b0), "r"(b1));
}

__device__ __forceinline__ float sigmoidf_(float x) {
    float t;
    asm("tanh.approx.f32 %0, %1;" : "=f"(t) : "f"(0.5f * x));
    return fmaf(t, 0.5f, 0.5f);
}
__device__ __forceinline__ float gelu2x(float x) {
    float u = x * fmaf(x * x, 0.7978845608028654f * 0.044715f, 0.7978845608028654f);
    float t;
    asm("tanh.approx.f32 %0, %1;" : "=f"(t) : "f"(u));
    return fmaf(x, t, x);
}
__device__ __forceinline__ float rbf(float x) { return bf_lo(pack_bf16(x, 0.f)); }

__device__ __forceinline__ uint32_t vsel(uint32_t a, uint32_t b, uint32_t p) {
    uint32_t r;
    asm volatile("{\n.reg .pred q;\nsetp.ne.u32 q, %3, 0;\nselp.b32 %0, %1, %2, q;\n}\n" : "=r"(r) : "r"(a), "r"(b), "r"(p));
    return r;
}
template <int R> __device__ __forceinline__ void rot_a(uint32_t (&x)[16][2], uint32_t p1) {
    const uint32_t last = x[15][R];
#pragma unroll
    for (int i = 15; i > 0; i--) x[i][R] = vsel(x[i - 1][R], x[i][R], p1);
    x[0][R] = vsel(last, x[0][R], p1);
}
template <int R> __device__ __forceinline__ void rot_b(uint32_t (&o)[16][2], const uint32_t (&t)[16][2], uint32_t p2) {
#pragma unroll
    for (int i = 0; i < 16; i++) o[i][R] = vsel(t[(i + 14) & 15][R], t[i][R], p2);
}
template <int U, int NA> __device__ __forceinline__ void x_store(const float (&xa)[NA], uint32_t (&W)[16][2]) {
#pragma unroll
    for (int t = 0; t < 4; t++)
#pragma unroll
        for (int r = 0; r < 2; r++) W[4 * t + U][r] = pack_bf16(xa[4 * t + r], xa[4 * t + 2 + r]);
}
template <int NA> __device__ __forceinline__ void x_store3(const float (&xa)[NA], uint32_t (&X3)[4][2]) {
#pragma unroll
    for (int t = 0; t < 4; t++)
#pragma unroll
        for (int r = 0; r < 2; r++) X3[t][r] = pack_bf16(xa[4 * t + r], xa[4 * t + 2 + r]);
}

template <int I> struct IC { static constexpr int v = I; };
template <int B, int E, class Fn> __device__ __forceinline__ void static_for(Fn&& f) {
    if constexpr (B < E) {
        f(IC<B>{});
        static_for<B + 1, E>(f);
    }
}

struct Rows {
    const uint8_t* src[8];
    __device__ __forceinline__ void from_reg(int v, const uint8_t* src0) {
        static_for<0, 8>([&](auto jc) {
            asm volatile("{\n.reg .u32 t;\nshfl.sync.idx.b32 t, %1, %3, 0x181f, 0xffffffff;\nmad.wide.u32 %0, t, 256, %2;\n}\n"
                         : "=l"(src[decltype(jc)::v]) : "r"(v), "l"(src0), "n"(decltype(jc)::v));
        });
    }
    __device__ __forceinline__ void from_smem(uint32_t a, const uint8_t* src0) {
        const uint4 v0 = lds128(a), v1 = lds128(a + 16);
        const uint32_t v[8] = {v0.x, v0.y, v0.z, v0.w, v1.x, v1.y, v1.z, v1.w};
#pragma unroll
        for (int j = 0; j < 8; j++) asm volatile("mad.wide.u32 %0, %1, 256, %2;" : "=l"(src[j]) : "r"(v[j]), "l"(src0));
    }
    template <int GS, int OFF> __device__ __forceinline__ void copy(uint32_t a0) {
        uint32_t a1 = a0 ^ 64;
        asm volatile("" : "+r"(a0), "+r"(a1));
#pragma unroll
        for (int j = 0; j < 8; j++) cpasync16(((j & 1) ? a1 : a0) + (j >> 1) * GS + (j & 1) * 512, src[j] + OFF);
    }
};

constexpr uint32_t PREP_IN = 0, PREP_OUT = 1352 * 80 + 384;
__device__ __forceinline__ void prep_work(int q, int warp, int lane, uint8_t* sm, const unsigned short* __restrict__ se_w1,
                                          const unsigned short* __restrict__ se_w2, const uint8_t* __restrict__ w_bi,
                                          const uint8_t* __restrict__ w_cross, const uint8_t* __restrict__ w_deep1,
                                          const unsigned short* __restrict__ w_deep2) {
    const int tid = warp * 32 + lane, wid = q * 12 + warp;
    const uint32_t sb = smem_u32(sm);
    if (warp == 11) {
        const uint8_t* p = w_deep1 + (size_t)(q >> 1) * 13 * 65536 + (q & 1) * 32768;
        asm volatile("{\n.reg .pred p;\nelect.sync _|p, 0xffffffff;\n@p cp.async.bulk.prefetch.L2.global [%0], 8192;\n}\n" ::"l"(w_bi + q * 8192) : "memory");
        const uint32_t t0 = (uint32_t)clock();
#pragma unroll 1
        for (int k = 0; k < 13; k++) {
            asm volatile("{\n.reg .pred p;\nelect.sync _|p, 0xffffffff;\n@p cp.async.bulk.prefetch.L2.global [%0], 32768;\n}\n" ::"l"(p + k * 65536) : "memory");
            while ((int)((uint32_t)clock() - t0) < (k ? k + 1 : 0) * W1_PACE) {}
        }
    } else {
        const uint32_t t0 = (uint32_t)clock();
        while ((int)((uint32_t)clock() - t0) < PREP_DELAY) __nanosleep(200);
#pragma unroll 1
        for (int i = tid; i < 1352 * 4; i += 352)
            cpasync16(sb + PREP_IN + (i >> 2) * 80 + (i & 3) * 16, w_cross + (size_t)(i >> 2) * 256 + q * 64 + (i & 3) * 16);
        if (warp < 8) {
            const int jj = 2 * q + (warp >> 2);
            const unsigned short* p = reinterpret_cast<const unsigned short*>(w_bi) + (16 * jj + 2 * (lane & 3)) * 128 + 64 + 16 * (warp & 3) + (lane >> 2);
            uint32_t f[4];
#pragma unroll
            for (int x = 0; x < 4; x++) {
                const unsigned short* pp = p + (x >> 1) * 8 * 128 + (x & 1) * 8;
                f[x] = (uint32_t)__ldg(pp) | ((uint32_t)__ldg(pp + 128) << 16);
            }
            g_WF[jj * 128 + (warp & 3) * 32 + lane] = make_uint4(f[0], f[1], f[2], f[3]);
        }
        asm volatile("cp.async.wait_all;" ::: "memory");
        asm volatile("bar.sync 1, 352;" ::: "memory");
        const int j = lane < 24 ? (4 * (lane >> 3) + ((lane >> 1) & 3) + 13 * (lane & 1)) : (lane == 24 ? 12 : 25);
        const bool valid = lane < 27 && lane != 25;
#pragma unroll 1
        for (int item = warp; item < 32; item += 11) {
            const int pq = item >> 4, t = (item >> 2) & 3, s = item & 3;
            const int R = 27 * pq + lane;
            const uint8_t* src = sm + PREP_IN + (pq * 676 + 4 * s * 26 + j) * 80 + t * 16;
            uint8_t* dst = sm + PREP_OUT + 2 * t * GBYTES + R * 128;
            uint4 L[4], H[4];
#pragma unroll
            for (int u = 0; u < 4; u++) {
                L[u] = make_uint4(0, 0, 0, 0);
                H[u] = L[u];
                if (valid && (u == 0 || s < 3)) {
                    L[u] = *reinterpret_cast<const uint4*>(src + u * 26 * 80);
                    H[u] = *reinterpret_cast<const uint4*>(src + (u + 13) * 26 * 80);
                }
            }
#pragma unroll
            for (int kap = 0; kap < 4; kap++) {
                uint32_t e[4][2];
#pragma unroll
                for (int cc = 0; cc < 4; cc++) {
                    const int u = (kap - cc) & 3;
                    const uint32_t l = kap == 0 ? L[u].x : kap == 1 ? L[u].y : kap == 2 ? L[u].z : L[u].w;
                    const uint32_t h = kap == 0 ? H[u].x : kap == 1 ? H[u].y : kap == 2 ? H[u].z : H[u].w;
                    e[cc][0] = __byte_perm(l, h, 0x5410);
                    e[cc][1] = __byte_perm(l, h, 0x7632);
                }
                if (lane < 27) {
                    uint8_t* d2 = dst + kap * (GBYTES / 2);
                    const int sw = (R + 54 * (kap & 1)) & 7;
                    *reinterpret_cast<uint4*>(d2 + (((2 * s) ^ sw) << 4)) = make_uint4(e[0][0], e[0][1], e[1][0], e[1][1]);
                    *reinterpret_cast<uint4*>(d2 + (((2 * s + 1) ^ sw) << 4)) = make_uint4(e[2][0], e[2][1], e[3][0], e[3][1]);
                }
            }
        }
        fence_async();
        asm volatile("bar.sync 1, 352;" ::: "memory");
        if (tid < 8) {
            uint8_t* gd = reinterpret_cast<uint8_t*>(g_G) + (size_t)((q >> 1) * 16 + tid * 2 + (q & 1)) * GBYTES;
            asm volatile("cp.async.bulk.global.shared::cta.bulk_group [%0], [%1], %2;" ::"l"(gd), "r"(sb + PREP_OUT + tid * GBYTES), "r"(GBYTES) : "memory");
            asm volatile("cp.async.bulk.commit_group;" ::: "memory");
            asm volatile("cp.async.bulk.wait_group 0;" ::: "memory");
        }
    }
    if (wid < 8) {
        const int g = lane >> 2, c = lane & 3;
        uint32_t f[2];
#pragma unroll
        for (int x = 0; x < 2; x++) {
            const int q = 2 * wid + x;
            const unsigned short* p;
            int st;
            bool v0, v1;
            if (wid < 4) {
                const int k = 4 * (q & 3) + 3 - c, n = 8 * (q >> 2) + g;
                p = se_w1 + k * 13 + n;
                st = 13 * 13;
                v0 = v1 = k < 13 && n < 13;
            } else {
                const int k = 4 * (wid - 4) + (g >> 1), m = 8 * x + 2 * c;
                p = se_w2 + m * 26 + k + 13 * (g & 1);
                st = 26;
                v0 = k < 13 && m < 13;
                v1 = k < 13 && m + 1 < 13;
            }
            const uint32_t lo = v0 ? __ldg(p) : 0, hh = v1 ? __ldg(p + st) : 0;
            f[x] = lo | (hh << 16);
        }
        uint8_t* m = reinterpret_cast<uint8_t*>(g_MISC);
        *reinterpret_cast<uint2*>(m + (wid >> 1) * 512 + lane * 16 + (wid & 1) * 8) = make_uint2(f[0], f[1]);
        reinterpret_cast<float*>(m + 2048)[wid * 32 + lane] =
            0.5f * __uint_as_float((uint32_t)__ldg(w_deep2 + wid * 32 + (lane & 16) + ((lane >> 1) & 1) * 8 + ((lane >> 2) & 3) * 2 + (lane & 1)) << 16);
    }
}

__global__ void __cluster_dims__(2, 1, 1) __launch_bounds__(NTHREADS, 1)
fibinet_kernel(const int* __restrict__ idx, const uint8_t* __restrict__ table, const uint8_t* __restrict__ w_bi,
               __nv_bfloat16* __restrict__ out,
               const unsigned short* __restrict__ se_w1, const unsigned short* __restrict__ se_w2,
               const uint8_t* __restrict__ w_cross, const uint8_t* __restrict__ w_deep1, const unsigned short* __restrict__ w_deep2,
               const __grid_constant__ CUtensorMap tmW1) {
    extern __shared__ __align__(1024) uint8_t smem_raw[];
    const int tid = threadIdx.x, lane = tid & 31;
    const int cta = (int)blockIdx.x - NPREP, rank = cta & 1;
    int id0 = 0, id1 = 0;
    if (cta >= 0 && tid < 256) {
        const int* p = idx + (((cta & ~1) + ((tid >> 5) & 1)) * 32 + (tid >> 6) * 8 + (lane >> 3)) * 26 + 13 * rank;
        id0 = ldi<0>(p);
        id1 = ldi<4 * 26>(p);
    }
    const int warp = uni(tid >> 5);
    if (cta < 0) {
        prep_work(blockIdx.x, warp, lane, smem_raw, se_w1, se_w2, w_bi, w_cross, w_deep1, w_deep2);
        if (warp < 11) {
            asm volatile("fence.proxy.async;" ::: "memory");
            __threadfence();
            asm volatile("bar.sync 1, 352;" ::: "memory");
            if (tid == 0) asm volatile("red.release.gpu.global.add.u32 [%0], %1;" ::"l"(&g_ready), "r"(NCTA / NPREP) : "memory");
        }
        return;
    }
    const uint32_t sb = uni(smem_u32(smem_raw));
    const uint32_t bar = sb + OFF_BAR;

    if (warp >= 8) {
        const int q = lane >> 3, ch = lane & 7;
        const uint8_t* src0 = table + ch * 16;
        asm volatile("" : "+l"(src0));
        asm volatile("setmaxnreg.dec.sync.aligned.u32 40;");
        if (tid == 256) {
#pragma unroll
            for (int i = 0; i < 8; i++) mbar_init(bar + (B_WFULL + i) * 8, 1);
#pragma unroll
            for (int i = 0; i < 10; i++) mbar_init(bar + (B_YDONE + i) * 8, i < 6 ? 8 : 1);
            asm volatile("mbarrier.arrive.expect_tx.shared::cta.b64 _, [%0], 512;" ::"r"(bar + B_DL * 8) : "memory");
            asm volatile("mbarrier.arrive.expect_tx.shared::cta.b64 _, [%0], 16384;" ::"r"(bar + B_XCHF * 8) : "memory");
            asm volatile("fence.mbarrier_init.release.cluster;" ::: "memory");
        }
        __syncwarp();
        asm volatile("barrier.cluster.arrive.relaxed.aligned;" ::: "memory");
        if (warp == 8) {
            fence_async();
            TR(0);
            const int krow0 = rank * 13 * 128;
            uint32_t target = 0;
#pragma unroll 1
            for (int S = 0; S < 16; S++) {
                if (S == 8) asm volatile("bar.sync 2, 384;" ::: "memory");
                tma3d_elect(sb + (S < 8 ? OFF_WR : OFF_WS1 - 65536) + S * 8192, &tmW1, krow0 + S * 16, bar + (S < 8 ? B_WFULL + S : B_WS1) * 8);
            }
            asm volatile("{\n.reg .pred p;\nelect.sync _|p, 0xffffffff;\n@p atom.relaxed.gpu.global.inc.u32 %0, [%1], 0xffffffff;\n}\n"
                         : "+r"(target) : "l"(&g_epoch) : "memory");
#pragma unroll 1
            for (int k = 2; k < 13; k++) {
                static_for<0, 8>([&](auto sc) {
                    constexpr int S = decltype(sc)::v;
                    mbar_wait(bar + (B_WEMPTY + S) * 8, k & 1);
                    tma3d_elect(sb + OFF_WR + S * 8192, &tmW1, krow0 + k * 128 + S * 16, bar + (B_WFULL + S) * 8);
                });
            }
            {
                target = (uni(target) & ~(uint32_t)(NCTA - 1)) + NCTA;
                asm volatile(
                    "{\n.reg .pred p;\n.reg .u32 c, v;\n.reg .s32 d;\nmov.u32 c, 0;\n"
                    "LW:\nld.acquire.gpu.global.u32 v, [%0];\nsub.s32 d, v, %1;\nsetp.ge.s32 p, d, 0;\n@p bra LD;\n"
                    "add.u32 c, c, 1;\nsetp.lt.u32 p, c, 1000000;\n@p bra LW;\ntrap;\nLD:\n}\n" ::"l"(&g_ready), "r"(target) : "memory");
                asm volatile("fence.proxy.async;" ::: "memory");
            }
            mbar_wait(bar + B_DFULL * 8, 1);
            bulk_elect(sb + OFF_SE, g_MISC, 3072, bar + B_MISC * 8);
            TR(1);
        } else {
            const uint32_t ix = sb + (warp < 11 ? OFF_IX1 + (warp - 9) * 1792 : OFF_IX2);
            {
                const uint8_t* g = reinterpret_cast<const uint8_t*>(idx + (cta & ~1) * 32 * 26) + (tid - 288) * 16;
                const uint32_t raw = sb + OFF_E0 + 12 * 8192;
#pragma unroll
                for (int i = 0; i < 5; i++)
                    if (i < 4 || warp == 9) cpasync16(raw + i * 1536 + (tid - 288) * 16, g + i * 1536);
                const int rho = 4 * ch + q, s0 = (warp - 9) * 16 + (rho >> 4) * 8 + (rho & 7), par = (lane >> 1) & 1;
                const uint32_t r1 = raw + (warp < 11 ? (par * 32 + s0) * 26 + 13 * rank : (rank * 32 + rho) * 26 + 13 - 13 * rank) * 4;
                const uint32_t r12 = raw + ((rank * 32 + (s0 & 31)) * 26 + 13 * par + 12) * 4;
                asm volatile("cp.async.wait_all;" ::: "memory");
                asm volatile("bar.sync 3, 96;" ::: "memory");
                uint32_t t[14];
#pragma unroll
                for (int k = 0; k < 14; k++) asm volatile("ld.shared.u32 %0, [%1];" : "=r"(t[k]) : "r"(k < 13 ? r1 + k * 4 : r12) : "memory");
#pragma unroll
                for (int k = 0; k < 14; k++)
                    if (k < 13 || warp < 11) asm volatile("st.shared.u32 [%0], %1;" ::"r"(ix + k * 128 + lane * 4), "r"(t[k]) : "memory");
                asm volatile("bar.sync 2, 384;" ::: "memory");
            }
            if (warp < 11) {
                const uint32_t rowoff = sb + q * 128 + (warp - 9) * 4096 + ((ch ^ q) << 4);
                cpasync_arrive(bar + B_DFULL * 8);
                Rows r;
                r.from_smem(ix + q * 32 + 128, src0);
                uint32_t tn;
                asm volatile("{\n.reg .u64 t;\nmov.u64 t, %1;\nmov.u32 %0, %%clock;\n}\n" : "=r"(tn) : "l"(r.src[7]));
                tn -= G1O;
                TR(2);
#pragma unroll 1
                for (int k = 1; k < 13; k++) {
                    const uint32_t t = rowoff ^ ((k & 3) << 5);
                    if (k > 3) mbar_wait(bar + (B_XDONE + (k & 3)) * 8, ((k >> 2) & 1) ^ 1);
                    else while ((int)((uint32_t)clock() - tn) < k * G1_PACE) {}
                    TR(2 + 2 * k);
                    if (k < 4) r.copy<1024, 0>(t + OFF_E0 + k * 8192);
                    r.copy<1024, 128>(t + OFF_R1 + (k & 3) * 8192);
                    if (k < 4) cpasync_arrive(bar + (B_DFULL + k) * 8);
                    auto pf = [&](int row) {
                        asm volatile("{\n.reg .u32 t;\n.reg .u64 a;\nld.shared.u32 t, [%0];\nmad.wide.u32 a, t, 256, %1;\n"
                                     "prefetch.global.L2 [a];\nprefetch.global.L2 [a+128];\n}\n" ::"r"(ix + row * 128 + lane * 4), "l"(src0) : "memory");
                    };
                    r.from_smem(ix + q * 32 + (k + 1) * 128, src0);
                    if (k < 12) {
                        if (k >= 3) {
                            if (k == 3) {
                                while ((int)((uint32_t)clock() - tn) < 4 * G1_PACE) {}
                                pf(4);
                                mbar_wait(bar + (B_DDONE + 1) * 8, 0);
                            }
                            r.copy<1024, 0>((rowoff ^ (((k + 1) & 3) << 5)) + OFF_E0 + (k + 1) * 8192);
                        }
                    }
                    if (k >= 3) cpasync_arrive(bar + (k == 3 ? B_DH4 : B_DFULL + (k & 3)) * 8);
                    if (k == 3) while ((int)((uint32_t)clock() - tn) < 5 * G1_PACE) {}
                    if (k >= 3 && k < 11) pf(k + 2);
                }
                mbar_wait(bar + B_HDONE * 8, 1);
                r.copy<1024, 128>(rowoff + OFF_X12);
                cpasync_arrive(bar + B_DH4 * 8);
            } else {
                const uint32_t rowoff = sb + q * 128 + (1 - rank) * 1024 + ((ch ^ q) << 4);
                Rows r;
                r.from_smem(ix + q * 32, src0);
#pragma unroll 1
                for (int k = 0; k < 13; k++) {
                    const uint32_t u = k & 3, ph = (k >> 2) & 1;
                    const uint32_t b0 = (rowoff ^ (u << 5)) + u * 8192;
                    mbar_wait(bar + (B_HDONE + u) * 8, ph);
                    r.copy<2048, 0>(b0 + OFF_E0 + (k >> 2) * 32768);
                    if (k < 12) {
                        mbar_wait(bar + (B_DDONE + u) * 8, ph);
                        TR(2 + 2 * k);
                        r.copy<2048, 128>(b0 + OFF_R1);
                    }
                    cpasync_arrive(bar + (B_XFULL + u) * 8);
                    if (k < 12) r.from_smem(ix + q * 32 + (k + 1) * 128, src0);
                }
                mbar_wait(bar + B_MISC * 8, 0);
            }
        }
        {
            const int hh = warp & 1, tp = (warp >> 1) & 1;
            const int* pi = idx + (cta * 32 + hh * 16 + ((lane >> 2) & 1) * 8 + (lane & 1) * 4 + q) * 26 + 13 * ((lane >> 1) & 1);
            int v[7];
            v[0] = ldi<8>(pi + (tp ? 0 : 4));
            v[1] = ldi<9>(pi + tp);
            v[2] = ldi<0>(pi + (tp ? 0 : 11));
            static_for<3, 7>([&](auto ic) { v[decltype(ic)::v] = ldi<2 * decltype(ic)::v - 5>(pi + tp); });
            asm volatile("barrier.cluster.wait.acquire.aligned;" ::: "memory");
            const uint32_t rowoff = sb + OFF_E1 + q * 128 + hh * 4096 + ((ch ^ q) << 4);
            const uint8_t* gsrc = reinterpret_cast<const uint8_t*>(g_G) + hh * GBYTES;
            const uint32_t gb = bar + hh * 8;
#pragma unroll 1
            for (int eta = 0; eta < 2; eta++) {
                const uint32_t gd0 = sb + hh * GSLOT + (eta ? OFF_G1 : OFF_G0), gd1 = gd0 + (eta ? G1_WRAP : 0);
                if (hh == tp) {
                    mbar_sleep(bar + (eta ? B_YDONE : B_XDONE + 3) * 8, 0);
                    fence_async();
                    bulk_elect(gd0, gsrc, GBYTES, gb + B_GFULL * 8);
                    bulk_elect(gd0 + 2 * GSLOT, gsrc + 2 * GBYTES, GBYTES, gb + (B_GFULL + 2) * 8);
                    mbar_wait(bar + (eta ? B_YD2 : B_EPI) * 8, 0);
                    fence_async();
                    bulk_elect(gd1 + 4 * GSLOT, gsrc + 4 * GBYTES, GBYTES, gb + (B_GFULL + 4) * 8);
                    bulk_elect(gd1 + 6 * GSLOT, gsrc + 6 * GBYTES, GBYTES, gb + (B_GFULL + 6) * 8);
                    static_for<0, 4>([&](auto nc) {
                        constexpr int N = 2 * decltype(nc)::v;
                        mbar_sleep(gb + (B_GEMPTY + N) * 8, eta);
                        bulk_elect((N < 4 ? gd0 : gd1) + N * GSLOT, gsrc + (8 + N) * GBYTES, GBYTES, gb + (B_GFULL + N) * 8);
                    });
                    gsrc += 16 * GBYTES;
                }
                if (eta) break;
#pragma unroll 1
                for (int n = tp; n < 13; n += 2) {
                    const int k = n ? n - 1 : 12;
                    Rows r;
                    r.from_reg(v[0], src0);
#pragma unroll
                    for (int i = 0; i < 6; i++) v[i] = v[i + 1];
                    mbar_sleep(bar + (n ? B_LAST + ((k + 3 + (k > 4)) >> 2) : B_EPI) * 8, 0);
                    r.copy<1024, 128>((rowoff ^ ((k & 3) << 5)) + k * 8192);
                    if (n == 1 && hh == 0) bulk_elect(sb + OFF_WF, g_WF, 16384, bar + B_WF * 8);
                    if (n) cpasync_arrive(bar + (B_YFULL + (k >> 1)) * 8);
                }
                TR(31);
            }
            asm volatile("cp.async.wait_all;" ::: "memory");
            if (warp == 8) mbar_sleep(bar + (B_LAST + 3) * 8, 1);
        }
    } else {
#pragma unroll
        for (int i = 0; i < 4; i++) {
            const int d = i * 32 + (tid >> 3), ch = tid & 7;
            cpasync16(sb + OFF_WTMP + d * 128 + ((ch ^ (d & 7)) << 4), w_bi + d * 256 + ch * 16);
        }
        asm volatile("cp.async.commit_group;" ::: "memory");
        {
            const uint32_t count = 1u << ((0x63335270u >> (4 * warp)) & 7);
            if (lane == 0) {
#pragma unroll
                for (int i = 0; i < 8; i++) mbar_init(bar + warp * 64 + i * 8, count);
                asm volatile("fence.mbarrier_init.release.cluster;" ::: "memory");
            }
            __syncwarp();
            asm volatile("barrier.cluster.arrive.relaxed.aligned;" ::: "memory");
        }
        if ((sb & 0x3FFFFu) != SBASE) __trap();
        asm volatile("setmaxnreg.inc.sync.aligned.u32 232;");
        TR(0);
        const int lane = vmov(tid & 31, uni(0u));
        const int wg = warp >> 2, w = warp & 3, g = lane >> 2, c = lane & 3;

        {
            const uint8_t *s0, *s1;
            asm volatile("mad.wide.u32 %0, %2, 256, %4;\nmad.wide.u32 %1, %3, 256, %4;" : "=l"(s0), "=l"(s1) : "r"(id0), "r"(id1), "l"(table + (lane & 7) * 16));
            const uint32_t d0 = sb + warp * 1024 + (lane >> 3) * 128 + (((lane & 7) ^ (lane >> 3)) << 4);
            cpasync16(d0 + OFF_E0, s0);
            cpasync16(d0 + OFF_R1, s0 + 128);
            cpasync16((d0 ^ 64) + OFF_E0 + 512, s1);
            cpasync16((d0 ^ 64) + OFF_R1 + 512, s1 + 128);
            asm volatile("cp.async.commit_group;" ::: "memory");
            asm volatile("bar.sync 2, 384;" ::: "memory");
            asm volatile("cp.async.wait_group 1;" ::: "memory");
            asm volatile("bar.sync 1, 256;" ::: "memory");
            {
                uint32_t r[4][4];
#pragma unroll
                for (int i = 0; i < 4; i++) ldsm4t(r[i][0], r[i][1], r[i][2], r[i][3], sb + OFF_WTMP + (i * 32 + lane) * 128 + ((warp ^ (lane & 7)) << 4));
                asm volatile("bar.sync 1, 256;" ::: "memory");
                const int row = 40 * (warp >> 2) + 8 * (warp & 3) + (lane & 7);
#pragma unroll
                for (int i = 0; i < 4; i++) {
                    const uint32_t a = sb + OFF_WT + (i >> 1) * 10240 + row * 128 + ((((i & 1) * 4 + (lane >> 3)) ^ (lane & 7)) << 4);
                    stsm4(a, r[i][0], r[i][1], r[i][2], r[i][3]);
                    if ((warp & 3) == 0) {
                        const uint32_t one = 0x3F803F80u;
                        const bool o = g >= 6;
                        stsm4(a + 32 * 128, o ? one : r[i][0], o ? one : r[i][1], o ? one : r[i][2], o ? one : r[i][3]);
                    }
                }
            }
        }
        asm volatile("barrier.cluster.wait.acquire.aligned;" ::: "memory");
        TR(1);

        const uint32_t uWR = uni(wg * (4096 >> 4)), uWT = uni(wg * (40 * 128 >> 4));
        const uint32_t p1 = c & 1, p2 = c & 2;

        uint32_t X[3][16][2], X3[4][2];
        uint32_t aw[3][4], aw3;
        {
            float dacc[64];
            float xa[20];
            uint32_t W[16][2], Z[4] = {0u, 0u, 0u, 0u}, zc = 0;
            uint32_t rbar;
            asm volatile("mapa.shared::cluster.u32 %0, %1, %2;" : "=r"(rbar) : "r"(bar), "r"(rank ^ 1));
            auto d_mma = [&](auto koc, auto jc, auto first, uint32_t kb) {
                constexpr int KO = decltype(koc)::v, J = decltype(jc)::v;
                constexpr uint32_t AO = (J < 4 ? OFF_E0 + KO * 8192 : OFF_R1 + (KO & 3) * 8192) + (((J & 3) ^ (KO & 3)) * 32);
                wgmma_deep<(decltype(first)::v != 1), AO, (decltype(first)::v == 2 ? OFF_WS1 : OFF_WR) + J * 8192>(dacc, J < 4 ? kb : 0u, uWR);
            };
            auto x_acc = [&](float (&acc)[20], auto koc, auto j0, auto j1, uint32_t kb) {
                constexpr int KO = decltype(koc)::v;
                static_for<decltype(j0)::v, decltype(j1)::v>([&](auto jc) {
                    constexpr int J = decltype(jc)::v;
                    constexpr uint32_t AO = (J < 4 ? OFF_E0 + KO * 8192 : KO == 12 ? OFF_X12 : OFF_R1 + (KO & 3) * 8192) + (((J & 3) ^ (KO & 3)) * 32);
                    constexpr uint32_t BO = OFF_WT + (J >> 2) * 10240 + (KO & 3) * 256 + (J & 3) * 32;
                    wgmma_x40<(J > 0), AO, BO>(acc, J < 4 ? kb : 0u, uWT);
                });
            };
            auto x_part = [&](auto koc, auto j0, auto j1, uint32_t kb) { x_acc(xa, koc, j0, j1, kb); };
            auto x_fin = [&](auto uc) {
                constexpr int U = decltype(uc)::v;
                x_store<U>(xa, W);
                const uint32_t zw = pack_bf16(xa[16] * (1.0f / 128.0f), xa[18] * (1.0f / 128.0f));
                zc = (c == 3 - U) ? zw : zc;
            };
            cwait<0>(bar + B_WFULL * 8);
            asm volatile("cp.async.wait_group 0;" ::: "memory");
            fence_async();
            asm volatile("bar.sync 1, 256;" ::: "memory");
            TR(2); TG(100);
            static_for<0, 8>([&](auto jc) {
                constexpr int J = decltype(jc)::v;
                wg_fence();
                d_mma(IC<0>{}, jc, IC<(J == 0)>{}, 0u);
                wg_commit();
                const uint32_t ok = probe(bar + (J < 7 ? B_WFULL + J + 1 : B_WS1) * 8, 0);
                if (J != 0) {
                    wg_wait<1>();
                    arrive0(bar + (B_WEMPTY + J - 1) * 8, lane);
                }
                if (J == 4) arrive1(bar + B_HDONE * 8, lane);
                confirm(ok, bar + (J < 7 ? B_WFULL + J + 1 : B_WS1) * 8, 0);
            });
            wg_wait<0>();
            arrive0(bar + (B_WEMPTY + 7) * 8, lane);
            arrive1(bar + B_DDONE * 8, lane);
            TR3(51);
            TR3(55);
            cwait<0>(bar + (B_DFULL + 1) * 8);
            fence_acq();
            TR3(52);
            wg_fence();
            static_for<0, 4>([&](auto jc) { d_mma(IC<1>{}, jc, IC<2>{}, 0u); });
            wg_commit();
            static_for<4, 8>([&](auto jc) { d_mma(IC<1>{}, jc, IC<2>{}, 0u); });
            wg_commit();
            wg_wait<1>();
            arrive1(bar + (B_HDONE + 1) * 8, lane);
            cwait<1>(bar + B_WFULL * 8);
            TR3(53);
            cwait<0>(bar + (B_DFULL + 2) * 8);
            fence_acq();
            TR(3); TG(101);
            static_for<0, 3>([&](auto jc) {
                constexpr int J = decltype(jc)::v;
                wg_fence();
                d_mma(IC<2>{}, jc, IC<0>{}, 0u);
                wg_commit();
                if (J == 0) {
                    wg_wait<1>();
                    arrive1(bar + (B_DDONE + 1) * 8, lane);
                }
                cwait<1>(bar + (B_WFULL + J + 1) * 8);
            });
            wg_wait<2>();
            arrive0(bar + B_WEMPTY * 8, lane);
            cwait<0>(bar + B_XFULL * 8);
            fence_acq();
#pragma unroll 1
            for (int s = 0; s < 3; s++) {
                const uint32_t kb = s * 2048, ph = s & 1;
                static_for<0, 4>([&](auto uc) {
                    constexpr int U = decltype(uc)::v;
                    if (U < 2 || s < 2) {
                        const uint32_t dph = U < 1 ? ph : ph ^ 1, xph = U < 3 ? ph : ph ^ 1;
                        static_for<3, 7>([&](auto jc) {
                            constexpr int J = decltype(jc)::v;
                            constexpr uint32_t NB = (B_WFULL + J + 1) * 8, NP = (U + 1) & 1;
                            wg_fence();
                            x_part(uc, IC<2 * J - 6>{}, IC<2 * J - 4>{}, kb);
                            d_mma(IC<U + 2>{}, jc, IC<0>{}, kb);
                            wg_commit();
                            if constexpr (J == 3) {
                                wg_wait<2>();
                                arrive1(bar + (B_WEMPTY + 1) * 8, lane);
                            }
                            if constexpr (U == 0 && J < 5) {
                                if (s > 0) rot_a<(J & 1)>(W, p1);
                            }
                            if constexpr (U == 0 && J >= 5) {
                                if (s == 1) rot_b<(J & 1)>(X[0], W, p2);
                                else if (s == 2) rot_b<(J & 1)>(X[1], W, p2);
                            }
                            if constexpr (U < 2 && J == 6) {
                                if (s == 0) {
                                    cwait<0>(bar + (U == 0 ? B_DFULL + 3 : B_DH4) * 8);
                                    fence_acq();
                                }
                            }
                            const uint32_t ok = probe(bar + NB, NP);
                            wg_wait<1>();
                            arrive0(bar + (B_WEMPTY + J - 1) * 8, lane);
                            if constexpr (J == 4) arrive1(bar + (B_HDONE + ((U + 2) & 3)) * 8, lane);
                            confirm(ok, bar + NB, NP);
                        });
                        {
                            uint32_t ok = probe(bar + B_WFULL * 8, U & 1);
                            wg_fence();
                            d_mma(IC<U + 2>{}, IC<7>{}, IC<0>{}, kb);
                            wg_commit();
                            confirm(ok, bar + B_WFULL * 8, U & 1);
                            wg_fence();
                            d_mma(IC<U + 3>{}, IC<0>{}, IC<0>{}, kb);
                            wg_commit();
                            ok = probe(bar + (B_WFULL + 1) * 8, U & 1);
                            wg_wait<2>();
                            reg_fence(xa);
                            arrive0(bar + (B_WEMPTY + 6) * 8, lane);
                            arrive1(bar + (B_XDONE + U) * 8, lane);
                            TR(5 + 3 * U + (kb >> 9) * 3);
                            if (U == 1) TG(102 + (kb >> 11));
                            confirm(ok, bar + (B_WFULL + 1) * 8, U & 1);
                            wg_fence();
                            d_mma(IC<U + 3>{}, IC<1>{}, IC<0>{}, kb);
                            wg_commit();
                            ok = probe(bar + (B_WFULL + 2) * 8, U & 1);
                            x_fin(uc);
                            if constexpr (U == 3) {
                                Z[0] = Z[1];
                                Z[1] = zc;
                            }
                            wg_wait<2>();
                            arrive0(bar + (B_WEMPTY + 7) * 8, lane);
                            arrive1(bar + (B_DDONE + ((U + 2) & 3)) * 8, lane);
                            confirm(ok, bar + (B_WFULL + 2) * 8, U & 1);
                            const uint32_t okx = probe(bar + (B_XFULL + ((U + 1) & 3)) * 8, xph);
                            const uint32_t okd = probe(bar + (B_DFULL + ((U + 3) & 3)) * 8, dph);
                            wg_fence();
                            d_mma(IC<U + 3>{}, IC<2>{}, IC<0>{}, kb);
                            wg_commit();
                            ok = probe(bar + (B_WFULL + 3) * 8, U & 1);
                            wg_wait<2>();
                            arrive0(bar + B_WEMPTY * 8, lane);
                            confirm(okx, bar + (B_XFULL + ((U + 1) & 3)) * 8, xph);
                            confirm(okd, bar + (B_DFULL + ((U + 3) & 3)) * 8, dph);
                            fence_acq();
                            confirm(ok, bar + (B_WFULL + 3) * 8, U & 1);
                        }
                    }
                });
            }
            static_for<3, 8>([&](auto jc) {
                constexpr int J = decltype(jc)::v;
                uint32_t ok = 1;
                if constexpr (J < 7) ok = probe(bar + (B_WFULL + J + 1) * 8, 1);
                wg_fence();
                d_mma(IC<12>{}, jc, IC<0>{}, 0u);
                wg_commit();
                if constexpr (J == 5 || J == 7) wg_wait<2>();
                if constexpr (J == 5) arrive0(bar + B_HDONE * 8, lane);
                if constexpr (J == 7) mbar_arrive_remote_elect(rbar + B_CANSEND * 8);
                if constexpr (J < 7) confirm(ok, bar + (B_WFULL + J + 1) * 8, 1);
            });
            float xc[20];
            wg_fence();
            x_part(IC<10>{}, IC<0>{}, IC<4>{}, 0u);
            wg_commit();
            cwait<0>(bar + (B_XFULL + 3) * 8);
            fence_acq();
            mbar_wait_cluster(bar + B_CANSEND * 8, 0);
            wg_wait<1>();
            reg_fence(dacc);
            TR(35);
            wg_fence();
            x_part(IC<10>{}, IC<4>{}, IC<8>{}, 0u);
            wg_commit();
            {
                const uint32_t rbuf = rbar + (OFF_XCH - OFF_BAR) + (warp * 32 + lane) * 16;
                uint32_t sd[16];
                if (rank) {
#pragma unroll
                    for (int i = 0; i < 16; i++) sd[i] = vpack(dacc[2 * i], dacc[2 * i + 1]);
                } else {
#pragma unroll
                    for (int i = 0; i < 16; i++) sd[i] = vpack(dacc[32 + 2 * i], dacc[33 + 2 * i]);
                }
                TR3(56);
                wg_fence();
                static_for<0, 4>([&](auto jc) {
                    constexpr int j = decltype(jc)::v;
                    x_acc(xc, IC<11>{}, IC<j>{}, IC<j + 1>{}, 0u);
                    asm volatile("st.async.shared::cluster.mbarrier::complete_tx::bytes.v4.b32 [%0], {%1,%2,%3,%4}, [%5];" ::"r"(rbuf + j * 4096),
                                 "r"(sd[4 * j]), "r"(sd[4 * j + 1]), "r"(sd[4 * j + 2]), "r"(sd[4 * j + 3]), "r"(rbar + B_XCHF * 8) : "memory");
                });
                wg_commit();
            }
            {
                const uint32_t ok0 = probe(bar + B_XFULL * 8, 1), ok1 = probe(bar + B_DH4 * 8, 1);
                wg_wait<1>();
                reg_fence(xa);
                wg_fence();
                x_acc(xc, IC<11>{}, IC<4>{}, IC<8>{}, 0u);
                wg_commit();
                x_fin(IC<2>{});
                confirm(ok0, bar + B_XFULL * 8, 1);
                confirm(ok1, bar + B_DH4 * 8, 1);
                fence_acq();
                TR3(58);
            }
            wg_fence();
            x_part(IC<12>{}, IC<0>{}, IC<3>{}, 0u);
            wg_commit();
            const uint32_t okm = probe(bar + B_MISC * 8, 0);
            wg_wait<1>();
            reg_fence(xc);
            TR(40); TG(105);
            arrive0(bar + (B_XDONE + 3) * 8, lane);
            const uint32_t yes = uni(1u);
            wg_fence();
            x_part(IC<12>{}, IC<3>{}, IC<4>{}, 0u);
            x_store<3>(xc, W);
            Z[2] = (c == 0) ? pack_bf16(xc[16] * (1.0f / 128.0f), xc[18] * (1.0f / 128.0f)) : zc;
            if (yes) rot_a<0>(W, p1);
            wg_fence();
            x_part(IC<12>{}, IC<4>{}, IC<6>{}, 0u);
            if (yes) rot_a<1>(W, p1);
            wg_fence();
            x_part(IC<12>{}, IC<6>{}, IC<8>{}, 0u);
            wg_commit();
            confirm(okm, bar + B_MISC * 8, 0);
            TR3(59);
            {
                const uint4 f0 = lds128(sb + OFF_SE + lane * 16), f1 = lds128(sb + OFF_SE + 512 + lane * 16);
                if (yes) rot_b<0>(X[2], W, p2);
                wg_wait<0>();
                reg_fence(xa);
                TR(42);
                Z[3] = (c == 3) ? pack_bf16(xa[16] * (1.0f / 128.0f), xa[18] * (1.0f / 128.0f)) : 0u;
                float h0[4] = {0.f, 0.f, 0.f, 0.f}, h1[4] = {0.f, 0.f, 0.f, 0.f};
                mma16816(h0, Z[0], Z[1], f0.x, f0.y);
                mma16816(h1, Z[0], Z[1], f1.x, f1.y);
                mma16816(h0, Z[2], Z[3], f0.z, f0.w);
                mma16816(h1, Z[2], Z[3], f1.z, f1.w);
                const uint4 f2 = lds128(sb + OFF_SE + 1024 + lane * 16), f3 = lds128(sb + OFF_SE + 1536 + lane * 16);
                rot_b<1>(X[2], W, p2);
                x_store3(xa, X3);
                const uint32_t r0 = pack_bf16(h0[0], h0[1]), r1 = pack_bf16(h1[0], h1[1]);
                const uint32_t ha = pack_bf16(0.5f * gelu2x(bf_lo(r0)), 0.5f * gelu2x(bf_hi(r0)));
                const uint32_t hb = pack_bf16(0.5f * gelu2x(bf_lo(r1)), 0.5f * gelu2x(bf_hi(r1)));
                float o[4][4];
#pragma unroll
                for (int s = 0; s < 4; s++) o[s][0] = o[s][1] = o[s][2] = o[s][3] = 0.f;
                mma16816(o[0], ha, hb, f2.x, f2.y);
                mma16816(o[1], ha, hb, f2.z, f2.w);
                mma16816(o[2], ha, hb, f3.x, f3.y);
                mma16816(o[3], ha, hb, f3.z, f3.w);
                TR3(60);
                mbar_wait_cluster(bar + B_XCHF * 8, 0);
                TR3(61);
                float hx[32];
                uint4 rv[4], wv[4];
#pragma unroll
                for (int j = 0; j < 4; j++) rv[j] = lds128(sb + OFF_XCH + (warp * 32 + lane) * 16 + j * 4096);
#pragma unroll
                for (int j = 0; j < 4; j++) wv[j] = lds128(sb + OFF_W2 + wg * 512 + rank * 256 + c * 16 + j * 64);
                __syncwarp();
                arrive0(bar + B_EPI * 8, lane);
                uint32_t ow[4];
#pragma unroll
                for (int s = 0; s < 4; s++) {
                    const uint32_t r = pack_bf16(o[s][0], o[s][1]);
                    ow[s] = vpack(sigmoidf_(bf_lo(r)), sigmoidf_(bf_hi(r)));
                }
                auto addup = [&](const float* d) {
#pragma unroll
                    for (int j = 0; j < 4; j++) {
                        const uint32_t vv[4] = {rv[j].x, rv[j].y, rv[j].z, rv[j].w};
#pragma unroll
                        for (int x = 0; x < 4; x++) {
                            hx[8 * j + 2 * x] = vadd(d[8 * j + 2 * x], bf_lo(vv[x]));
                            hx[8 * j + 2 * x + 1] = vadd(d[8 * j + 2 * x + 1], bf_hi(vv[x]));
                        }
                    }
                };
                if (rank) addup(&dacc[32]);
                else addup(&dacc[0]);
                TR3(62);
#pragma unroll
                for (int s = 0; s < 3; s++)
#pragma unroll
                    for (int kap = 0; kap < 4; kap++) aw[s][kap] = __shfl_sync(0xffffffffu, ow[s], (kap - c) & 3, 4);
                aw3 = __shfl_sync(0xffffffffu, ow[3], 0, 4);
                float dl0 = 0.f, dl1 = 0.f;
#pragma unroll
                for (int j = 0; j < 4; j++) {
                    const float w0 = __uint_as_float(wv[j].x), w1 = __uint_as_float(wv[j].y), w2 = __uint_as_float(wv[j].z), w3 = __uint_as_float(wv[j].w);
                    const float* h = &hx[8 * j];
                    dl0 = fmaf(gelu2x(h[0]), w0, fmaf(gelu2x(h[1]), w1, fmaf(gelu2x(h[4]), w2, fmaf(gelu2x(h[5]), w3, dl0))));
                    dl1 = fmaf(gelu2x(h[2]), w0, fmaf(gelu2x(h[3]), w1, fmaf(gelu2x(h[6]), w2, fmaf(gelu2x(h[7]), w3, dl1))));
                }
                float dl = (p1 ? dl1 : dl0) + __shfl_xor_sync(0xffffffffu, p1 ? dl0 : dl1, 1);
                dl += __shfl_xor_sync(0xffffffffu, dl, 2);
                asm volatile(
                    "{\n.reg .pred p;\n.reg .u32 a, b;\nsetp.lt.u32 p, %3, 2;\n"
                    "mapa.shared::cluster.u32 a, %0, %4;\nmapa.shared::cluster.u32 b, %1, %4;\n"
                    "@p st.async.shared::cluster.mbarrier::complete_tx::bytes.f32 [a], %2, [b];\n}\n"
                    ::"r"(sb + OFF_RES + ((rank * 2 + wg) * 32 + w * 8 + g) * 4), "r"(bar + B_DL * 8), "f"(dl), "r"(c), "r"(p1) : "memory");
            }
        }
        TR(46); TG(106);

        float accp[3] = {0.f, 0.f, 0.f}, accq[7] = {0.f, 0.f, 0.f, 0.f, 0.f, 0.f, 0.f};
        uint32_t eb0 = sb + OFF_E0 + w * 2048 + g * 128 + c * 8192 + ((((4 * wg) ^ g) ^ (2 * c)) << 4);
        uint32_t eb2 = eb0 + 8 * 8192;
        uint32_t eb3 = sb + OFF_E0 + 12 * 8192 + w * 2048 + g * 128 + (c & 1) * 1024 + (((4 * wg) ^ g) << 4);

#pragma unroll 1
        for (int eta = 0; eta < 2; eta++) {
            uint64_t dG = ((uint64_t)uni(DESC_HI) << 32) | uni(wg * (GSLOT >> 4) + (uint32_t)(eta ? cdesc(OFF_G1, 16) : cdesc(OFF_G0, 16)));
            const uint32_t gbar = uni(bar + wg * 8), uz = uni(0u);
            constexpr int JS = 2 * (int)GSLOT - 3 * 3456 - 64;
            const uint32_t iK = uz + 4, iM = uz + (3456 - 64) / 16, iS = uz + JS / 16;
            const uint32_t iH = uni(JS / 16 + eta * (G1_WRAP / 16)), iW = 2 * iS - 8 * (GSLOT / 16) - iH;
            if (eta == 1) {
                float xb[2][32];
                uint4 wf[8];
                const uint32_t okw = probe(bar + B_WF * 8, 0);
                cwait<0>(bar + B_YFULL * 8);
                fence_acq();
                confirm(okw, bar + B_WF * 8, 0);
#pragma unroll
                for (int j = 0; j < 8; j++) wf[j] = lds128(sb + OFF_WF + w * 512 + j * 2048 + lane * 16);
                const uint32_t uE = uni(wg * ((8192 + 32) >> 4)), uO = uni(wg * ((8192 - 32) >> 4));
                uint32_t lb[4] = {0u, 0u, 0u, 0u}, lm = 0, stb = 0, l3 = 0;
                auto y_mma = [&](auto ic, auto jc) {
                    constexpr int I = decltype(ic)::v, J = decltype(jc)::v;
                    constexpr int KB = I < 0 ? 12 : I < 2 ? 8 + 2 * I : 2 * I - 4, PB = I < 0 ? 12 : 2 * I, POS = (J & 3) ^ (KB & 3);
                    constexpr uint32_t BO = (J < 4 ? OFF_E0 + KB * 8192 : OFF_E1 + PB * 8192) + POS * 32;
                    wgmma_t64<(J > 0), BO>(xb[I & 1], wf[J], (POS & 1) ? uO : uE);
                };
                auto y_sync = [&](auto ic) {
                    reg_fence(xb[decltype(ic)::v & 1]);
                    if (decltype(ic)::v == 2) asm volatile("bar.sync 1, 256;" ::: "memory");
                    else if (wg == 0) asm volatile("bar.sync 4, 128;" ::: "memory");
                    else asm volatile("bar.sync 5, 128;" ::: "memory");
                };
                auto y_st = [&](auto ic, int qq) {
                    constexpr int I = decltype(ic)::v, KB = I < 0 ? 12 : I < 2 ? 8 + 2 * I : 2 * I - 4;
                    const float* d = &xb[I & 1][8 * qq];
                    if (I >= 0 || wg == 0)
                        stsm4((stb ^ ((qq ^ (KB & 3)) << 5)) + KB * 8192, pack_bf16(d[0], d[1]), pack_bf16(d[2], d[3]),
                              pack_bf16(d[4], d[5]), pack_bf16(d[6], d[7]));
                };
                auto ld_addr = [&]() {
                    const uint32_t ln = vmov(lane, uz);
                    const uint32_t lc = (ln >> 1) & 3, r = (ln >> 3) & 1;
                    const uint32_t base = sb + OFF_E0 + (32 * wg + r) * 128 + (((2 * w + (ln & 1)) ^ r) << 4);
                    lm = ln >> 4;
#pragma unroll
                    for (int kap = 0; kap < 4; kap++) {
                        const uint32_t u = (kap - lc) & 3;
                        lb[kap] = (base ^ ((kap ^ u) << 5)) + u * 8192 + lm * 2048 + kap * 256;
                    }
                    l3 = (base ^ (lc << 5)) + 12 * 8192 + lc * 256 + lm * 1024;
                    asm volatile("" : "+r"(lb[0]), "+r"(lb[1]), "+r"(lb[2]), "+r"(lb[3]), "+r"(l3));
                };
                auto x23_load = [&](auto nc) {
                    constexpr int n = decltype(nc)::v;
                    if constexpr (n < 8) ldsm4t(X[2][n][0], X[2][n][1], X[2][n + 8][0], X[2][n + 8][1], lb[n & 3] + 65536 + (n >> 2) * 1024);
                    else ldsm4t(X3[2 * n - 16][0], X3[2 * n - 16][1], X3[2 * n - 15][0], X3[2 * n - 15][1], l3 + (n - 8) * 2048);
                };
                auto y_step = [&](auto ic) {
                    constexpr int I = decltype(ic)::v;
                    wg_fence();
                    y_mma(ic, IC<0>{});
                    uint32_t ok = 0;
                    if constexpr (I < 5) ok = probe(bar + (B_YFULL + I + 1) * 8, 0);
                    y_mma(ic, IC<1>{});
                    y_mma(ic, IC<2>{});
                    wg_commit();
                    if constexpr (I == 2) ld_addr();
                    if constexpr (I < 5) {
                        TR6(100 + 4 * I);
                        confirm(ok, bar + (B_YFULL + I + 1) * 8, 0);
                        TR6(101 + 4 * I);
                        fence_acq();
                    }
                    if constexpr (I == 4) {
                        __syncwarp();
                        arrive0(bar + B_YDONE * 8, lane);
                    }
                    wg_wait<1>();
                    TR6(102 + 4 * I);
                    y_sync(IC<I - 1>{});
                    wg_fence();
                    static_for<3, 8>([&](auto jc) {
                        constexpr int J = decltype(jc)::v;
                        y_mma(ic, jc);
                        if constexpr (J < 7) y_st(IC<I - 1>{}, J - 3);
                        if constexpr (I == 3) { x23_load(IC<2 * J - 6>{}); x23_load(IC<2 * J - 5>{}); }
                    });
                    wg_commit();
                    TR3(92 + I);
                };
                TR3(90);
#pragma unroll
                for (int i = 0; i < 32; i++) xb[1][i] = 0.f;
                wg_fence();
                if (wg == 0) static_for<0, 8>([&](auto jc) { y_mma(IC<-1>{}, jc); });
                wg_commit();
                {
                    const uint32_t ln = vmov(lane, uz);
                    stb = sb + OFF_E0 + wg * 8192 + (16 * w + (ln & 15)) * 128 + (((ln >> 4) ^ (ln & 7) ^ (2 * wg)) << 4);
                }
                cwait<0>(bar + (B_LAST + 3) * 8);
                y_step(IC<0>{});
                y_step(IC<1>{});
                y_step(IC<2>{});
                y_step(IC<3>{});
                y_step(IC<4>{});
                y_step(IC<5>{});
                mbar_wait_cluster(bar + B_DL * 8, 0);
                wg_wait<0>();
                y_sync(IC<5>{});
#pragma unroll
                for (int qq = 0; qq < 4; qq++) y_st(IC<5>{}, qq);
                TR3(98);
                asm volatile("bar.sync 1, 256;" ::: "memory");
#pragma unroll
                for (int pi = 0; pi < 16; pi++)
                    ldsm4t(X[0][pi][0], X[0][pi][1], X[1][pi][0], X[1][pi][1], lb[pi & 3] + lm * (32768 - 2048) + (pi >> 2) * 1024);
                __syncwarp();
                arrive0(bar + B_YD2 * 8, lane);
                eb0 += OFF_E1 - OFF_E0 + 4 * 8192;
                eb2 += OFF_E1 - OFF_E0 - 8 * 8192;
                eb3 += OFF_E1 - OFF_E0;
                TR(48); TG(108);
            }
            float P[16], Q[16];
            uint4 ev[7];
            const uint32_t meta = vmov(0xEEEE4444u, uz);
            auto e_load = [&](auto tc) {
                constexpr int T = decltype(tc)::v;
#pragma unroll
                for (int t = 0; t < 2; t++) {
                    ev[2 * t] = lds128((eb0 ^ (T << 4)) + t * 4 * 8192);
                    ev[2 * t + 1] = lds128((eb0 ^ (T << 4)) + t * 4 * 8192 + 1024);
                }
                ev[4] = lds128(eb2 ^ (T << 4));
                ev[5] = lds128((eb2 ^ (T << 4)) + 1024);
                ev[6] = lds128(eb3 ^ (T << 4));
            };
            auto p_issue = [&](auto pc) {
                constexpr int PI = decltype(pc)::v, T = PI >> 2;
                const uint32_t m0 = vmov(X[2][PI][0], uz), m1 = vmov(X[2][PI][1], uz), m2 = X3[T][0] | uz, m3 = X3[T][1] | uz;
                wg_fence();
                wgmma_sp<0>(P, X[0][PI][0], X[0][PI][1], X[1][PI][0], X[1][PI][1], dG, meta, iK);
                wgmma_sp<1>(P, m0, m1, m2, m3, dG, meta, iM);
                wg_commit();
            };
            auto q_issue = [&](auto pc) {
                constexpr int PI = decltype(pc)::v, T = PI >> 2, KA = PI & 3;
                const uint32_t q0 = hmul2(X[0][PI][0], aw[0][KA]), q1 = hmul2(X[0][PI][1], aw[0][KA]);
                const uint32_t q2 = hmul2(X[1][PI][0], aw[1][KA]), q3 = hmul2(X[1][PI][1], aw[1][KA]);
                const uint32_t q4 = hmul2(X[2][PI][0], aw[2][KA]), q5 = hmul2(X[2][PI][1], aw[2][KA]);
                const uint32_t q6 = hmul2(X3[T][0], aw3), q7 = hmul2(X3[T][1], aw3);
                wg_fence();
                wgmma_sp<0>(Q, q0, q1, q2, q3, dG, meta, iK);
                wgmma_sp<1>(Q, q4, q5, q6, q7, dG, meta, (PI & 1) == 0 ? iM : (PI & 3) == 1 ? iS : PI == 7 ? iW : iH);
                wg_commit();
            };
            cwait<0>(gbar + B_GFULL * 8);
            p_issue(IC<0>{});
            e_load(IC<0>{});
            q_issue(IC<0>{});
            static_for<0, 16>([&](auto pc) {
                constexpr int PI = decltype(pc)::v, T = PI >> 2, KA = PI & 3;
                constexpr uint32_t NB = (B_GFULL + ((PI + 1) & 7)) * 8, NP = ((PI + 1) >> 3) & 1;
                if (KA == 2) TR(64 + T * 6);
                float e0[7], e1[7];
#pragma unroll
                for (int sl = 0; sl < 7; sl++) {
                    const uint32_t wd = KA == 0 ? ev[sl].x : KA == 1 ? ev[sl].y : KA == 2 ? ev[sl].z : ev[sl].w;
                    e0[sl] = bf_lo(wd);
                    e1[sl] = bf_hi(wd);
                }
                wg_wait<1>();
                reg_fence(P);
#pragma unroll
                for (int sl = 0; sl < 7; sl++) {
                    const int i0 = 4 * (sl >> 1) + (sl & 1), pi = sl == 6 ? 2 : (sl & 1);
                    accp[pi] = fmaf(e1[sl], P[i0 + 2], fmaf(e0[sl], P[i0], accp[pi]));
                }
                if constexpr (PI < 15) {
                    if constexpr ((PI & 1) != 0) {
                        reg_fence(accp);
                        cwait<NP>(gbar + NB);
                    }
                    p_issue(IC<PI + 1>{});
                }
                if constexpr (KA == 3 && T < 3) e_load(IC<T + 1>{});
                if constexpr (PI < 15) wg_wait<1>(); else wg_wait<0>();
                reg_fence(Q);
                if constexpr ((PI & 1) != 0) arrive0(PI < 8 ? gbar + (B_GEMPTY + PI - 1) * 8 : bar + (B_LAST + (PI - 8) / 2) * 8, lane);
#pragma unroll
                for (int sl = 0; sl < 7; sl++) {
                    const int i0 = 4 * (sl >> 1) + (sl & 1);
                    accq[sl] = fmaf(e1[sl], Q[i0 + 2], fmaf(e0[sl], Q[i0], accq[sl]));
                }
                if constexpr (PI < 15) q_issue(IC<PI + 1>{});
            });
            if (eta == 0) { TR(47); TG(107); }
        }
        TR(49); TG(109);

        const uint32_t so = sb + (w * 8 + g) * 4;
        float dlv[4];
#pragma unroll
        for (int i = 0; i < 4; i++) asm volatile("ld.shared.f32 %0, [%1];" : "=f"(dlv[i]) : "r"(so + OFF_RES + i * 128) : "memory");
        float cv[4];
#pragma unroll
        for (int t = 0; t < 3; t++) {
            const uint32_t own = p1 ? aw[t][2] : aw[t][0];
            cv[t] = fmaf(bf_hi(own), accq[2 * t + 1], bf_lo(own) * accq[2 * t]);
        }
        const float last = fmaf(p1 ? bf_hi(aw3) : bf_lo(aw3), accq[6], accp[2]);
        float cr = ((accp[0] + accp[1]) + (p2 ? 0.f : last)) + ((cv[0] + cv[1]) + cv[2]);
        cr += __shfl_xor_sync(0xffffffffu, cr, 1);
        cr += __shfl_xor_sync(0xffffffffu, cr, 2);
        if (wg == 1) {
            asm volatile("st.shared.f32 [%0], %1;" ::"r"(so + OFF_IX2), "f"(cr) : "memory");
            asm volatile("bar.arrive 1, 256;" ::: "memory");
        } else {
            __nv_bfloat16* po = out + cta * 32 + w * 8 + g;
            const float rd = (dlv[0] + dlv[1]) + (dlv[2] + dlv[3]);
            asm volatile("bar.sync 1, 256;" ::: "memory");
            float c1;
            asm volatile("ld.shared.f32 %0, [%1];" : "=f"(c1) : "r"(so + OFF_IX2) : "memory");
            const float rc = cr + c1;
            if (c == 0) *po = __float2bfloat16(rbf(rc) + rbf(rd));
        }
        TR(50);
    }
}

typedef CUresult (*PFN_encodeTiled)(CUtensorMap*, CUtensorMapDataType, cuuint32_t, void*, const cuuint64_t*, const cuuint64_t*,
                                    const cuuint32_t*, const cuuint32_t*, CUtensorMapInterleave, CUtensorMapSwizzle,
                                    CUtensorMapL2promotion, CUtensorMapFloatOOBfill);

}

extern "C" void kernel_launch(void* const* d_in, const int* in_sizes, int n_in, void* d_out, int out_size) {
    (void)in_sizes; (void)n_in; (void)out_size;
    static PFN_encodeTiled enc = nullptr;
    if (!enc) {
        void* fn = nullptr;
        cudaDriverEntryPointQueryResult st;
        cudaGetDriverEntryPoint("cuTensorMapEncodeTiled", &fn, cudaEnableDefault, &st);
        enc = (PFN_encodeTiled)fn;
        cudaFuncSetAttribute(fibinet_kernel, cudaFuncAttributeMaxDynamicSharedMemorySize, SMEM_BYTES);
    }
    CUtensorMap tm;
    const cuuint64_t dims[3] = {64, 3328, 4};
    const cuuint64_t strides[2] = {512, 128};
    const cuuint32_t box[3] = {64, 16, 4};
    const cuuint32_t estr[3] = {1, 1, 1};
    enc(&tm, CU_TENSOR_MAP_DATA_TYPE_BFLOAT16, 3, d_in[6], dims, strides, box, estr, CU_TENSOR_MAP_INTERLEAVE_NONE,
        CU_TENSOR_MAP_SWIZZLE_128B, CU_TENSOR_MAP_L2_PROMOTION_L2_256B, CU_TENSOR_MAP_FLOAT_OOB_FILL_NONE);
    fibinet_kernel<<<NCTA + NPREP, NTHREADS, SMEM_BYTES>>>((const int*)d_in[0], (const uint8_t*)d_in[1], (const uint8_t*)d_in[4],
                                                          (__nv_bfloat16*)d_out,
                                                          (const unsigned short*)d_in[2], (const unsigned short*)d_in[3],
                                                          (const uint8_t*)d_in[5], (const uint8_t*)d_in[6], (const unsigned short*)d_in[7], tm);
}
```
